```python
import torch

def _softmax(x, axis=-1):
    return torch.softmax(x, dim=axis)
def _gelu(x):
    return torch.nn.functional.gelu(x, approximate="tanh")
def _silu(x):
    return torch.nn.functional.silu(x)
def _sigmoid(x):
    return torch.sigmoid(x)
def _layernorm(x, axis=-1, eps=1e-5):
    m = x.mean(dim=axis, keepdim=True)
    v = x.var(dim=axis, keepdim=True, unbiased=False)
    return (x - m) / torch.sqrt(v + eps)
def _scatter_add(tgt, idx, src, axis=0):
    return tgt.clone().index_add_(axis, idx, src)
def _segment_sum(src, seg, n):
    out = torch.zeros((n,) + src.shape[1:], dtype=src.dtype)
    return out.index_add_(0, seg, src)
def _pad(x, pw):
    flat = tuple(v for pair in reversed(pw) for v in pair)
    return torch.nn.functional.pad(x, flat)

kernel_name = 'gated_mix__sliding_block__glu_gated_glu__prompt'

def setup_inputs():

    _w = (lambda a: (lambda t: t.to(torch.bfloat16) if t.is_floating_point() else t)(torch.as_tensor(a)))
    def _A_setup():
        B, S, D = 1, 2048, 448
        return {
            "x": _w((lambda *s: torch.randn(*s, dtype=torch.bfloat16) * 0.05)(B, S, D)),
            "wqkv": _w((lambda *s: torch.randn(*s, dtype=torch.bfloat16) * 1.6)(D, 3 * D)),
            "wo": _w((lambda *s: torch.randn(*s, dtype=torch.bfloat16) * 0.05)(D, D)),
        }
    _A_in = _A_setup()

    def _B_setup():
        B, S, D, F = 1, 2048, 448, 1792
        return {
            "x": _w((lambda *s: torch.randn(*s, dtype=torch.bfloat16) * 0.05)(B, S, D)),
            "w_gate": _w((lambda *s: torch.randn(*s, dtype=torch.bfloat16) * 3.2)(D, F)),
            "w_up": _w((lambda *s: torch.randn(*s, dtype=torch.bfloat16) * 0.2)(D, F)),
            "w_down": _w((lambda *s: torch.randn(*s, dtype=torch.bfloat16) * 0.2)(F, D)),
        }
    _B_in = _B_setup()

    return {
        "A_x": _A_in["x"],
        "A_wqkv": _A_in["wqkv"],
        "A_wo": _A_in["wo"],
        "B_x": _B_in["x"],
        "B_w_gate": _B_in["w_gate"],
        "B_w_up": _B_in["w_up"],
        "B_w_down": _B_in["w_down"],
        "gate_w": _w((lambda *s: torch.randn(*s, dtype=torch.bfloat16) * 0.05)(448) * 16.0),
    }

def reference(A_x, A_wqkv, A_wo, B_x, B_w_gate, B_w_up, B_w_down, gate_w):
    def _A_ref(x, wqkv, wo):
        B, S, D = x.shape
        H = 16; Dh = D // H; W = 256
        qkv = (lambda x, *d: x.permute(*d))((x @ wqkv).reshape(B, S, 3, H, Dh), 2, 0, 3, 1, 4)
        q, k, v = qkv[0], qkv[1], qkv[2]
        scores = torch.einsum("bhqd,bhkd->bhqk", q, k) * (Dh ** -0.5)
        idx = torch.arange(S)
        mask = (idx[:, None] - idx[None, :] >= 0) & (idx[:, None] - idx[None, :] < W)
        scores = torch.where(mask[None, None], scores, -1e9)
        p = _softmax(scores, axis=-1)
        o = torch.einsum("bhqk,bhkd->bhqd", p, v)
        return (lambda x, *d: x.permute(*d))(o, 0, 2, 1, 3).reshape(B, S, D) @ wo

    def _B_ref(x, w_gate, w_up, w_down):
        g = torch.einsum("bsd,df->bsf", x, w_gate)
        u = torch.einsum("bsd,df->bsf", x, w_up)
        h = _sigmoid(g) * u
        return torch.einsum("bsf,fd->bsd", h, w_down)

    x = A_x
    g = _sigmoid((x * gate_w).sum(-1, keepdims=True))
    a = _A_ref(x, A_wqkv, A_wo)
    b = _B_ref(x, B_w_gate, B_w_up, B_w_down)
    return g * a + (1 - g) * b
```

```cpp
#include <cuda_runtime.h>
#include <cuda_bf16.h>
#include <cuda.h>
#include <stdint.h>

namespace {

constexpr int NSLOT = 4;
constexpr int XAHEAD = 3;
constexpr int XT = 2;
constexpr uint32_t SB = 0x400;
constexpr uint32_t OFF_X = SB;
constexpr uint32_t OFF_QO = OFF_X + 114688;
constexpr uint32_t OFF_KV = OFF_QO + 16384;
constexpr uint32_t OFF_E = OFF_QO;
constexpr uint32_t OFF_RING = OFF_KV + 32768;
constexpr uint32_t OFF_BAR = OFF_RING + NSLOT * 16384;
constexpr uint32_t OFF_G = OFF_BAR + 640;
constexpr uint32_t OFF_EPOCH = OFF_G + 512;
constexpr uint32_t OFF_GW = OFF_EPOCH + 32;
constexpr uint32_t OFF_TS = OFF_GW + 896;
constexpr uint32_t SMEM_BYTES = OFF_TS + 384 - SB;

constexpr uint32_t B_EFULL = OFF_BAR;
constexpr uint32_t B_FULL = B_EFULL + 8 * 4;
constexpr uint32_t B_KVFULL = B_FULL + 8 * NSLOT;
constexpr uint32_t B_ZOK = B_KVFULL + 8 * 2;
constexpr uint32_t B_SLOW = B_ZOK + 8;
constexpr uint32_t B_SETTLED = B_SLOW + 8;
constexpr uint32_t B_PUB = B_SETTLED + 8;
constexpr uint32_t B_GW = B_PUB + 8 * 3;
constexpr uint32_t B_GFULL = B_GW + 8 * 7;
constexpr uint32_t B_GO = B_GFULL + 8 * 3;
constexpr uint32_t B_EMPTY = B_GO + 8;
constexpr uint32_t B_EEMPTY = B_EMPTY + 8 * NSLOT;
constexpr uint32_t B_GEMPTY = B_EEMPTY + 8 * 4;
constexpr uint32_t B_VRDY = B_GEMPTY + 8 * 3;
constexpr uint32_t B_XFULL = B_VRDY + 8;
constexpr uint32_t B_KVEMPTY = B_XFULL + 8 * 7;
constexpr uint32_t B_QKRDY = B_KVEMPTY + 8 * 2;
constexpr uint32_t B_ORDY = B_QKRDY + 8 * 2;
constexpr uint32_t B_ZRDY = B_ORDY + 8 * 2;
constexpr uint32_t B_K1RDY = B_ZRDY + 8;
constexpr uint32_t B_END = B_K1RDY + 8;
static_assert(B_KVEMPTY % 16 == 0, "toggled with ^ 8");
static_assert(B_END <= OFF_G, "barriers overflow");

constexpr uint32_t DESC_HI = 0x40000040u;
constexpr uint32_t DESC_HI64 = 0x80000020u;
constexpr uint32_t SPIN_LIMIT = 1u << 22;
constexpr uint32_t QKV_STAGE_BYTES = 3 * 32 * 112;

constexpr int IT_P1 = 6, IT_P2 = 13, IT_P3 = 20, IT_P4 = 24;
constexpr uint32_t G2_BYTES = 36864;
constexpr int G2A = 4, G2B = 8;
__host__ __device__ constexpr uint32_t g2_buf(uint32_t i) { return i < 2 ? OFF_X + i * G2_BYTES : OFF_RING; }
__host__ __device__ constexpr uint32_t out_tile(uint32_t i) { return i < 5 ? OFF_X + 73728 + i * 8192 : OFF_RING + i * 8192; }

struct alignas(64) Maps {
  CUtensorMap x, qkv, g64, g32, u64, u32, down, down64, wo, out;
};

struct alignas(128) Exchange {
  uint8_t kv[2][16384];
  unsigned flag, epoch, pad[2];
};
__device__ Exchange g_ex[128];
__device__ unsigned g_zflag[16 * 8];
__device__ __forceinline__ const uint8_t* kv_block(int kb, int j) { return g_ex[(kb >> 1) * 8 + j].kv[kb & 1]; }
#define TS(i)
#define TA(i)

__device__ __forceinline__ uint32_t smem_u32(const void* p) { return (uint32_t)__cvta_generic_to_shared(p); }
extern __shared__ __align__(1024) uint8_t smem_raw[];
__device__ __forceinline__ void mbar_init(uint32_t bar, uint32_t cnt) {
  asm volatile("mbarrier.init.shared::cta.b64 [%0], %1;" ::"r"(bar), "r"(cnt) : "memory");
}
__device__ __forceinline__ void mbar_expect_tx(uint32_t bar, uint32_t bytes) {
  asm volatile("mbarrier.arrive.expect_tx.shared::cta.b64 _, [%0], %1;" ::"r"(bar), "r"(bytes) : "memory");
}
__device__ __forceinline__ void mbar_arrive(uint32_t bar) {
  asm volatile("mbarrier.arrive.shared::cta.b64 _, [%0];" ::"r"(bar) : "memory");
}
__device__ __forceinline__ void mbar_arrive_if(bool pred, uint32_t bar) {
  asm volatile("{\n.reg .pred p;\nsetp.ne.u32 p, %1, 0;\n@p mbarrier.arrive.shared::cta.b64 _, [%0];\n}" ::"r"(bar), "r"((uint32_t)pred) : "memory");
}
__device__ __forceinline__ void mbar_wait(uint32_t bar, uint32_t parity) {
  asm volatile(
      "{\n.reg .pred p;\n.reg .u32 n;\n"
      "mbarrier.try_wait.parity.shared::cta.b64 p, [%0], %1;\n"
      "@p bra DONE;\n"
      "mov.u32 n, 0;\n"
      "LOOP:\n"
      "mbarrier.try_wait.parity.shared::cta.b64 p, [%0], %1;\n"
      "@p bra DONE;\n"
      "add.u32 n, n, 1;\n"
      "setp.lt.u32 p, n, %2;\n"
      "@p bra LOOP;\n"
      "trap;\n"
      "DONE:\n}" ::"r"(bar), "r"(parity), "n"(SPIN_LIMIT) : "memory");
}
__device__ __forceinline__ uint32_t mbar_try(uint32_t bar, uint32_t parity) {
  uint32_t ok;
  asm volatile("{\n.reg .pred p;\nmbarrier.test_wait.parity.shared::cta.b64 p, [%1], %2;\nselp.u32 %0, 1, 0, p;\n}"
               : "=r"(ok) : "r"(bar), "r"(parity) : "memory");
  return ok;
}
__device__ __forceinline__ bool elect_one() {
  uint32_t ok;
  asm volatile("{\n.reg .pred p;\nelect.sync _|p, 0xffffffff;\nselp.u32 %0, 1, 0, p;\n}" : "=r"(ok));
  return ok != 0;
}
__device__ __forceinline__ void bulk_load(uint32_t dst, const void* src, uint32_t bytes, uint32_t bar) {
  asm volatile("cp.async.bulk.shared::cluster.global.mbarrier::complete_tx::bytes [%0], [%1], %2, [%3];"
               ::"r"(dst), "l"(src), "r"(bytes), "r"(bar) : "memory");
}
__device__ __forceinline__ void flag_wait(const unsigned* p, unsigned want) {
  unsigned v, n = 0;
  while (true) {
    asm volatile("ld.acquire.gpu.global.u32 %0, [%1];" : "=r"(v) : "l"(p) : "memory");
    if ((int)(v - want) >= 0) break;
    if (++n > SPIN_LIMIT) __trap();
  }
}
__device__ __forceinline__ void tma2d(uint32_t dst, const CUtensorMap* m, int c0, int c1, uint32_t bar) {
  asm volatile("cp.async.bulk.tensor.2d.shared::cluster.global.mbarrier::complete_tx::bytes [%0], [%1, {%3, %4}], [%2];"
               ::"r"(dst), "l"(m), "r"(bar), "r"(c0), "r"(c1) : "memory");
}
__device__ __forceinline__ void tma3d(uint32_t dst, const CUtensorMap* m, int c0, int c1, int c2, uint32_t bar) {
  asm volatile("cp.async.bulk.tensor.3d.shared::cluster.global.mbarrier::complete_tx::bytes [%0], [%1, {%3, %4, %5}], [%2];"
               ::"r"(dst), "l"(m), "r"(bar), "r"(c0), "r"(c1), "r"(c2) : "memory");
}
__device__ __forceinline__ void prefetch_map(const CUtensorMap* m) { asm volatile("prefetch.tensormap [%0];" ::"l"(m) : "memory"); }
__device__ __forceinline__ void wg_fence() { asm volatile("wgmma.fence.sync.aligned;" ::: "memory"); }
__device__ __forceinline__ void wg_commit() { asm volatile("wgmma.commit_group.sync.aligned;" ::: "memory"); }
template <int N> __device__ __forceinline__ void wg_wait() { asm volatile("wgmma.wait_group.sync.aligned %0;" ::"n"(N) : "memory"); }
template <int N> __device__ __forceinline__ void reg_fence(float (&d)[N]) {
#pragma unroll
  for (int i = 0; i < N; i++) asm volatile("" : "+f"(d[i])::"memory");
}
template <int N> __device__ __forceinline__ void reg_fence(uint32_t (&d)[N]) {
#pragma unroll
  for (int i = 0; i < N; i++) asm volatile("" : "+r"(d[i])::"memory");
}
__device__ __forceinline__ void fence_async_smem() { asm volatile("fence.proxy.async.shared::cta;" ::: "memory"); }
__device__ __forceinline__ void fence_async_global() { asm volatile("fence.proxy.async.global;" ::: "memory"); }
__device__ __forceinline__ uint32_t pack_bf16(float lo, float hi) {
  uint32_t r;
  asm("cvt.rn.bf16x2.f32 %0, %1, %2;" : "=r"(r) : "f"(hi), "f"(lo));
  return r;
}
__device__ __forceinline__ void sts32(uint32_t a, uint32_t v) { asm volatile("st.shared.u32 [%0], %1;" ::"r"(a), "r"(v) : "memory"); }
__device__ __forceinline__ void sts128(uint32_t a, uint32_t r0, uint32_t r1, uint32_t r2, uint32_t r3) {
  asm volatile("st.shared.v4.u32 [%0], {%1, %2, %3, %4};" ::"r"(a), "r"(r0), "r"(r1), "r"(r2), "r"(r3) : "memory");
}
__device__ __forceinline__ void stsm4(uint32_t a, uint32_t r0, uint32_t r1, uint32_t r2, uint32_t r3) {
  asm volatile("stmatrix.sync.aligned.m8n8.x4.shared.b16 [%0], {%1, %2, %3, %4};" ::"r"(a), "r"(r0), "r"(r1), "r"(r2), "r"(r3) : "memory");
}
__device__ __forceinline__ float lds_f32(uint32_t a) {
  float v;
  asm volatile("ld.shared.f32 %0, [%1];" : "=f"(v) : "r"(a) : "memory");
  return v;
}
__device__ __forceinline__ uint4 lds128(uint32_t a) {
  uint4 v;
  asm volatile("ld.shared.v4.u32 {%0, %1, %2, %3}, [%4];" : "=r"(v.x), "=r"(v.y), "=r"(v.z), "=r"(v.w) : "r"(a) : "memory");
  return v;
}
__device__ __forceinline__ float ex2(float x) {
  float y;
  asm("ex2.approx.ftz.f32 %0, %1;" : "=f"(y) : "f"(x));
  return y;
}
__device__ __forceinline__ float tanh_fast(float x) {
  float y;
  asm("tanh.approx.f32 %0, %1;" : "=f"(y) : "f"(x));
  return y;
}
__host__ __device__ constexpr uint32_t desc_lo(uint32_t addr, uint32_t lbo) { return ((addr & 0x3FFFFu) >> 4) | ((lbo >> 4) << 16); }
__device__ __forceinline__ void sched_fence() {
  asm volatile("pmevent 0;" ::: "memory");
}

__device__ __forceinline__ void mma_qkv(float (&d)[92], uint32_t alo, uint32_t blo, uint32_t bhi, int scale_d) {
  asm volatile("{\n.reg .pred p;\n.reg .b64 da, db;\nsetp.ne.b32 p, %95, 0;\nmov.b64 da, {%92, %96};\nmov.b64 db, {%93, %94};\n"
    "wgmma.mma_async.sync.aligned.m64n184k16.f32.bf16.bf16 {"
    "%0, %1, %2, %3, %4, %5, %6, %7, %8, %9, %10, %11, %12, %13, %14, %15, "
    "%16, %17, %18, %19, %20, %21, %22, %23, %24, %25, %26, %27, %28, %29, %30, %31, "
    "%32, %33, %34, %35, %36, %37, %38, %39, %40, %41, %42, %43, %44, %45, %46, %47, "
    "%48, %49, %50, %51, %52, %53, %54, %55, %56, %57, %58, %59, %60, %61, %62, %63, "
    "%64, %65, %66, %67, %68, %69, %70, %71, %72, %73, %74, %75, %76, %77, %78, %79, "
    "%80, %81, %82, %83, %84, %85, %86, %87, %88, %89, %90, %91"
    "}, da, db, p, 1, 1, 0, 1;\n}\n"
    : "+f"(d[0]), "+f"(d[1]), "+f"(d[2]), "+f"(d[3]), "+f"(d[4]), "+f"(d[5]), "+f"(d[6]), "+f"(d[7]),
      "+f"(d[8]), "+f"(d[9]), "+f"(d[10]), "+f"(d[11]), "+f"(d[12]), "+f"(d[13]), "+f"(d[14]), "+f"(d[15]),
      "+f"(d[16]), "+f"(d[17]), "+f"(d[18]), "+f"(d[19]), "+f"(d[20]), "+f"(d[21]), "+f"(d[22]), "+f"(d[23]),
      "+f"(d[24]), "+f"(d[25]), "+f"(d[26]), "+f"(d[27]), "+f"(d[28]), "+f"(d[29]), "+f"(d[30]), "+f"(d[31]),
      "+f"(d[32]), "+f"(d[33]), "+f"(d[34]), "+f"(d[35]), "+f"(d[36]), "+f"(d[37]), "+f"(d[38]), "+f"(d[39]),
      "+f"(d[40]), "+f"(d[41]), "+f"(d[42]), "+f"(d[43]), "+f"(d[44]), "+f"(d[45]), "+f"(d[46]), "+f"(d[47]),
      "+f"(d[48]), "+f"(d[49]), "+f"(d[50]), "+f"(d[51]), "+f"(d[52]), "+f"(d[53]), "+f"(d[54]), "+f"(d[55]),
      "+f"(d[56]), "+f"(d[57]), "+f"(d[58]), "+f"(d[59]), "+f"(d[60]), "+f"(d[61]), "+f"(d[62]), "+f"(d[63]),
      "+f"(d[64]), "+f"(d[65]), "+f"(d[66]), "+f"(d[67]), "+f"(d[68]), "+f"(d[69]), "+f"(d[70]), "+f"(d[71]),
      "+f"(d[72]), "+f"(d[73]), "+f"(d[74]), "+f"(d[75]), "+f"(d[76]), "+f"(d[77]), "+f"(d[78]), "+f"(d[79]),
      "+f"(d[80]), "+f"(d[81]), "+f"(d[82]), "+f"(d[83]), "+f"(d[84]), "+f"(d[85]), "+f"(d[86]), "+f"(d[87]),
      "+f"(d[88]), "+f"(d[89]), "+f"(d[90]), "+f"(d[91])
    : "r"(alo), "r"(blo), "r"(bhi), "r"(scale_d), "r"(DESC_HI));
}
__device__ __forceinline__ void mma_n128(float (&d)[64], uint32_t alo, uint32_t blo, uint32_t bhi, int scale_d) {
  asm volatile("{\n.reg .pred p;\n.reg .b64 da, db;\nsetp.ne.b32 p, %67, 0;\nmov.b64 da, {%64, %68};\nmov.b64 db, {%65, %66};\n"
    "wgmma.mma_async.sync.aligned.m64n128k16.f32.bf16.bf16 {"
    "%0, %1, %2, %3, %4, %5, %6, %7, %8, %9, %10, %11, %12, %13, %14, %15, "
    "%16, %17, %18, %19, %20, %21, %22, %23, %24, %25, %26, %27, %28, %29, %30, %31, "
    "%32, %33, %34, %35, %36, %37, %38, %39, %40, %41, %42, %43, %44, %45, %46, %47, "
    "%48, %49, %50, %51, %52, %53, %54, %55, %56, %57, %58, %59, %60, %61, %62, %63"
    "}, da, db, p, 1, 1, 0, 1;\n}\n"
    : "+f"(d[0]), "+f"(d[1]), "+f"(d[2]), "+f"(d[3]), "+f"(d[4]), "+f"(d[5]), "+f"(d[6]), "+f"(d[7]),
      "+f"(d[8]), "+f"(d[9]), "+f"(d[10]), "+f"(d[11]), "+f"(d[12]), "+f"(d[13]), "+f"(d[14]), "+f"(d[15]),
      "+f"(d[16]), "+f"(d[17]), "+f"(d[18]), "+f"(d[19]), "+f"(d[20]), "+f"(d[21]), "+f"(d[22]), "+f"(d[23]),
      "+f"(d[24]), "+f"(d[25]), "+f"(d[26]), "+f"(d[27]), "+f"(d[28]), "+f"(d[29]), "+f"(d[30]), "+f"(d[31]),
      "+f"(d[32]), "+f"(d[33]), "+f"(d[34]), "+f"(d[35]), "+f"(d[36]), "+f"(d[37]), "+f"(d[38]), "+f"(d[39]),
      "+f"(d[40]), "+f"(d[41]), "+f"(d[42]), "+f"(d[43]), "+f"(d[44]), "+f"(d[45]), "+f"(d[46]), "+f"(d[47]),
      "+f"(d[48]), "+f"(d[49]), "+f"(d[50]), "+f"(d[51]), "+f"(d[52]), "+f"(d[53]), "+f"(d[54]), "+f"(d[55]),
      "+f"(d[56]), "+f"(d[57]), "+f"(d[58]), "+f"(d[59]), "+f"(d[60]), "+f"(d[61]), "+f"(d[62]), "+f"(d[63])
    : "r"(alo), "r"(blo), "r"(bhi), "r"(scale_d), "r"(DESC_HI));
}
__device__ __forceinline__ void mma_rs64(float (&d)[32], uint32_t a0, uint32_t a1, uint32_t a2, uint32_t a3, uint32_t blo, uint32_t bhi, int scale_d) {
  asm volatile("{\n.reg .pred p;\n.reg .b64 db;\nsetp.ne.b32 p, %38, 0;\nmov.b64 db, {%36, %37};\n"
    "wgmma.mma_async.sync.aligned.m64n64k16.f32.bf16.bf16 {"
    "%0, %1, %2, %3, %4, %5, %6, %7, %8, %9, %10, %11, %12, %13, %14, %15, "
    "%16, %17, %18, %19, %20, %21, %22, %23, %24, %25, %26, %27, %28, %29, %30, %31"
    "}, {%32, %33, %34, %35}, db, p, 1, 1, 1;\n}\n"
    : "+f"(d[0]), "+f"(d[1]), "+f"(d[2]), "+f"(d[3]), "+f"(d[4]), "+f"(d[5]), "+f"(d[6]), "+f"(d[7]),
      "+f"(d[8]), "+f"(d[9]), "+f"(d[10]), "+f"(d[11]), "+f"(d[12]), "+f"(d[13]), "+f"(d[14]), "+f"(d[15]),
      "+f"(d[16]), "+f"(d[17]), "+f"(d[18]), "+f"(d[19]), "+f"(d[20]), "+f"(d[21]), "+f"(d[22]), "+f"(d[23]),
      "+f"(d[24]), "+f"(d[25]), "+f"(d[26]), "+f"(d[27]), "+f"(d[28]), "+f"(d[29]), "+f"(d[30]), "+f"(d[31])
    : "r"(a0), "r"(a1), "r"(a2), "r"(a3), "r"(blo), "r"(bhi), "r"(scale_d));
}
__device__ __forceinline__ void mma_ss64(float (&d)[32], uint32_t alo, uint32_t blo, uint32_t bhi, int scale_d) {
  asm volatile("{\n.reg .pred p;\n.reg .b64 da, db;\nsetp.ne.b32 p, %35, 0;\nmov.b64 da, {%32, %36};\nmov.b64 db, {%33, %34};\n"
    "wgmma.mma_async.sync.aligned.m64n64k16.f32.bf16.bf16 {"
    "%0, %1, %2, %3, %4, %5, %6, %7, %8, %9, %10, %11, %12, %13, %14, %15, "
    "%16, %17, %18, %19, %20, %21, %22, %23, %24, %25, %26, %27, %28, %29, %30, %31"
    "}, da, db, p, 1, 1, 0, 1;\n}\n"
    : "+f"(d[0]), "+f"(d[1]), "+f"(d[2]), "+f"(d[3]), "+f"(d[4]), "+f"(d[5]), "+f"(d[6]), "+f"(d[7]),
      "+f"(d[8]), "+f"(d[9]), "+f"(d[10]), "+f"(d[11]), "+f"(d[12]), "+f"(d[13]), "+f"(d[14]), "+f"(d[15]),
      "+f"(d[16]), "+f"(d[17]), "+f"(d[18]), "+f"(d[19]), "+f"(d[20]), "+f"(d[21]), "+f"(d[22]), "+f"(d[23]),
      "+f"(d[24]), "+f"(d[25]), "+f"(d[26]), "+f"(d[27]), "+f"(d[28]), "+f"(d[29]), "+f"(d[30]), "+f"(d[31])
    : "r"(alo), "r"(blo), "r"(bhi), "r"(scale_d), "r"(DESC_HI));
}
__device__ __forceinline__ void mma_s(float (&d)[32], uint32_t alo, uint32_t blo, uint32_t bhi, int scale_d) {
  asm volatile("{\n.reg .pred p;\n.reg .b64 da, db;\nsetp.ne.b32 p, %35, 0;\nmov.b64 da, {%32, %36};\nmov.b64 db, {%33, %34};\n"
    "wgmma.mma_async.sync.aligned.m64n64k16.f32.bf16.bf16 {"
    "%0, %1, %2, %3, %4, %5, %6, %7, %8, %9, %10, %11, %12, %13, %14, %15, "
    "%16, %17, %18, %19, %20, %21, %22, %23, %24, %25, %26, %27, %28, %29, %30, %31"
    "}, da, db, p, 1, 1, 0, 0;\n}\n"
    : "+f"(d[0]), "+f"(d[1]), "+f"(d[2]), "+f"(d[3]), "+f"(d[4]), "+f"(d[5]), "+f"(d[6]), "+f"(d[7]),
      "+f"(d[8]), "+f"(d[9]), "+f"(d[10]), "+f"(d[11]), "+f"(d[12]), "+f"(d[13]), "+f"(d[14]), "+f"(d[15]),
      "+f"(d[16]), "+f"(d[17]), "+f"(d[18]), "+f"(d[19]), "+f"(d[20]), "+f"(d[21]), "+f"(d[22]), "+f"(d[23]),
      "+f"(d[24]), "+f"(d[25]), "+f"(d[26]), "+f"(d[27]), "+f"(d[28]), "+f"(d[29]), "+f"(d[30]), "+f"(d[31])
    : "r"(alo), "r"(blo), "r"(bhi), "r"(scale_d), "r"(DESC_HI));
}
__device__ __forceinline__ void mma_s0(float (&d)[32], uint32_t alo, uint32_t blo, uint32_t bhi) {
  asm volatile("{\n.reg .pred p;\n.reg .b64 da, db;\nsetp.ne.b32 p, %35, 0;\nmov.b64 da, {%32, %36};\nmov.b64 db, {%33, %34};\n"
    "wgmma.mma_async.sync.aligned.m64n64k16.f32.bf16.bf16 {"
    "%0, %1, %2, %3, %4, %5, %6, %7, %8, %9, %10, %11, %12, %13, %14, %15, "
    "%16, %17, %18, %19, %20, %21, %22, %23, %24, %25, %26, %27, %28, %29, %30, %31"
    "}, da, db, p, 1, 1, 0, 0;\n}\n"
    : "=f"(d[0]), "=f"(d[1]), "=f"(d[2]), "=f"(d[3]), "=f"(d[4]), "=f"(d[5]), "=f"(d[6]), "=f"(d[7]),
      "=f"(d[8]), "=f"(d[9]), "=f"(d[10]), "=f"(d[11]), "=f"(d[12]), "=f"(d[13]), "=f"(d[14]), "=f"(d[15]),
      "=f"(d[16]), "=f"(d[17]), "=f"(d[18]), "=f"(d[19]), "=f"(d[20]), "=f"(d[21]), "=f"(d[22]), "=f"(d[23]),
      "=f"(d[24]), "=f"(d[25]), "=f"(d[26]), "=f"(d[27]), "=f"(d[28]), "=f"(d[29]), "=f"(d[30]), "=f"(d[31])
    : "r"(alo), "r"(blo), "r"(bhi), "n"(0), "r"(DESC_HI));
}
__device__ __forceinline__ void mma_pv(float (&d)[16], uint32_t a0, uint32_t a1, uint32_t a2, uint32_t a3, uint32_t blo, uint32_t bhi, int scale_d) {
  asm volatile("{\n.reg .pred p;\n.reg .b64 db;\nsetp.ne.b32 p, %22, 0;\nmov.b64 db, {%20, %21};\n"
    "wgmma.mma_async.sync.aligned.m64n32k16.f32.bf16.bf16 {"
    "%0, %1, %2, %3, %4, %5, %6, %7, %8, %9, %10, %11, %12, %13, %14, %15"
    "}, {%16, %17, %18, %19}, db, p, 1, 1, 1;\n}\n"
    : "+f"(d[0]), "+f"(d[1]), "+f"(d[2]), "+f"(d[3]), "+f"(d[4]), "+f"(d[5]), "+f"(d[6]), "+f"(d[7]),
      "+f"(d[8]), "+f"(d[9]), "+f"(d[10]), "+f"(d[11]), "+f"(d[12]), "+f"(d[13]), "+f"(d[14]), "+f"(d[15])
    : "r"(a0), "r"(a1), "r"(a2), "r"(a3), "r"(blo), "r"(bhi), "r"(scale_d));
}

__device__ __forceinline__ void store_heads(uint32_t rowaddr, uint32_t lane, const uint32_t (&v)[14], uint32_t pad) {
  const uint32_t q = lane & 3;
  uint32_t o[16];
#pragma unroll
  for (int c = 0; c < 8; c++)
#pragma unroll
    for (int hf = 0; hf < 2; hf++) {
      uint32_t x = c < 7 ? v[2 * c + hf] : pad;
      if ((c & 1) && c < 7) x = q == (7u - c) / 2 ? pad : x;
      if (c >= 2) x = q >= 4u - c / 2 ? v[2 * (c - 1) + hf] : x;
      o[2 * c + hf] = x;
    }
#pragma unroll
  for (int g = 0; g < 4; g++)
    stsm4(rowaddr + (((2 * g + (lane >> 4)) ^ (lane & 7)) << 4), o[4 * g], o[4 * g + 1], o[4 * g + 2], o[4 * g + 3]);
}

constexpr float SM_C = 0.18898223650461361f * 1.4426950408889634f;

struct RowStat {
  float m0, m1;
  float al0, al1;
};

__device__ __forceinline__ void mask_block(float (&s)[32], bool diag, int row, int q) {
  const float NEG = __int_as_float(0xff800000);
  const int t0 = row - 2 * q, t1 = t0 + 8;
#pragma unroll
  for (int g = 0; g < 8; g++) {
    if (((8 * g) <= t0) != diag) s[4 * g] = NEG;
    if (((8 * g + 1) <= t0) != diag) s[4 * g + 1] = NEG;
    if (((8 * g) <= t1) != diag) s[4 * g + 2] = NEG;
    if (((8 * g + 1) <= t1) != diag) s[4 * g + 3] = NEG;
  }
}

__device__ __forceinline__ void update_max(const float (&s)[32], RowStat& r, bool first) {
  const float p0 = first ? __int_as_float(0xff800000) : r.m0, p1 = first ? __int_as_float(0xff800000) : r.m1;
  float a0 = fmaxf(s[0], s[1]), a1 = fmaxf(s[2], s[3]), b0 = fmaxf(s[4], s[5]), b1 = fmaxf(s[6], s[7]);
#pragma unroll
  for (int g = 2; g < 8; g += 2) {
    a0 = fmaxf(a0, fmaxf(s[4 * g], s[4 * g + 1]));
    a1 = fmaxf(a1, fmaxf(s[4 * g + 2], s[4 * g + 3]));
    b0 = fmaxf(b0, fmaxf(s[4 * g + 4], s[4 * g + 5]));
    b1 = fmaxf(b1, fmaxf(s[4 * g + 6], s[4 * g + 7]));
  }
  a0 = fmaxf(fmaxf(a0, b0), p0);
  a1 = fmaxf(fmaxf(a1, b1), p1);
  a0 = fmaxf(a0, __shfl_xor_sync(~0u, a0, 1));
  a1 = fmaxf(a1, __shfl_xor_sync(~0u, a1, 1));
  a0 = fmaxf(a0, __shfl_xor_sync(~0u, a0, 2));
  a1 = fmaxf(a1, __shfl_xor_sync(~0u, a1, 2));
  r.al0 = ex2(p0 - a0);
  r.al1 = ex2(p1 - a1);
  r.m0 = a0;
  r.m1 = a1;
}

__device__ __forceinline__ void exp_shifted(float (&s)[32], float m0, float m1) {
#pragma unroll
  for (int g = 0; g < 8; g++) {
    s[4 * g] = ex2(s[4 * g] - m0);
    s[4 * g + 1] = ex2(s[4 * g + 1] - m0);
    s[4 * g + 2] = ex2(s[4 * g + 2] - m1);
    s[4 * g + 3] = ex2(s[4 * g + 3] - m1);
  }
}
template <int G0, int G1> __device__ __forceinline__ void ex2_groups(float (&s)[32]) {
#pragma unroll
  for (int i = 4 * G0; i < 4 * G1; i++) s[i] = ex2(s[i]);
}
constexpr int GX = 6;

__device__ __forceinline__ void issue_s(float (&s)[32], uint32_t qlo, uint32_t klo) {
  wg_fence();
  mma_s0(s, qlo, klo, DESC_HI);
  mma_s(s, qlo + 2, klo + 2, DESC_HI, 1);
  wg_commit();
  sched_fence();
}
__device__ __forceinline__ void issue_pv(float (&o)[16], const uint32_t (&p)[16], uint32_t vlo, int acc_o) {
  wg_fence();
  mma_pv(o, p[0], p[1], p[2], p[3], vlo, DESC_HI, acc_o);
  mma_pv(o, p[4], p[5], p[6], p[7], vlo + 128, DESC_HI, 1);
  mma_pv(o, p[8], p[9], p[10], p[11], vlo + 256, DESC_HI, 1);
  mma_pv(o, p[12], p[13], p[14], p[15], vlo + 384, DESC_HI, 1);
  wg_commit();
  sched_fence();
}
__device__ __forceinline__ void issue_s_pv(float (&s)[32], uint32_t qlo, uint32_t klo, float (&o)[16], const uint32_t (&p)[16],
                                           uint32_t vlo, int acc_o) {
  wg_fence();
  mma_pv(o, p[0], p[1], p[2], p[3], vlo, DESC_HI, acc_o);
  mma_pv(o, p[4], p[5], p[6], p[7], vlo + 128, DESC_HI, 1);
  mma_pv(o, p[8], p[9], p[10], p[11], vlo + 256, DESC_HI, 1);
  mma_pv(o, p[12], p[13], p[14], p[15], vlo + 384, DESC_HI, 1);
  mma_s0(s, qlo, klo, DESC_HI);
  mma_s(s, qlo + 2, klo + 2, DESC_HI, 1);
  wg_commit();
  sched_fence();
}
__device__ __forceinline__ float rcp_fast(float x) {
  float y;
  asm("rcp.approx.ftz.f32 %0, %1;" : "=f"(y) : "f"(x));
  return y;
}
__device__ __forceinline__ void pack_p(const float (&s)[32], uint32_t (&p)[16]) {
#pragma unroll
  for (int i = 0; i < 16; i++) p[i] = pack_bf16(s[2 * i], s[2 * i + 1]);
}
struct PMask { uint32_t d[4], t[3]; };
__device__ __forceinline__ void and_xor(uint32_t& p, uint32_t m, uint32_t inv) {
  asm("lop3.b32 %0, %0, %1, %2, 0x60;" : "+r"(p) : "r"(m), "r"(inv));
}
__device__ __forceinline__ void mask_p(uint32_t (&p)[16], const PMask& mk, uint32_t inv) {
#pragma unroll
  for (int k = 0; k < 4; k++) {
    and_xor(p[4 * k], mk.d[k], inv);
    and_xor(p[4 * k + 1], k == 0 ? ~0u : mk.t[k - 1], inv);
    and_xor(p[4 * k + 2], k == 3 ? 0u : mk.t[k], inv);
    and_xor(p[4 * k + 3], mk.d[k], inv);
  }
}

template <int NG, int N>
__device__ __forceinline__ void glu_group(uint32_t* h, const float (&acc)[N], int g, float a0, float a1) {
  const float* gt = acc + 4 * g;
  const float* up = acc + 4 * (NG + g);
  const float s0 = fmaf(a0, tanh_fast(0.5f * gt[0]), a0);
  const float s1 = fmaf(a0, tanh_fast(0.5f * gt[1]), a0);
  const float s2 = fmaf(a1, tanh_fast(0.5f * gt[2]), a1);
  const float s3 = fmaf(a1, tanh_fast(0.5f * gt[3]), a1);
  h[2 * g] = pack_bf16(s0 * up[0], s1 * up[1]);
  h[2 * g + 1] = pack_bf16(s2 * up[2], s3 * up[3]);
  asm volatile("" : "+r"(h[2 * g]), "+r"(h[2 * g + 1])::"memory");
}

template <int IT0, int HS0, class Side>
__device__ __forceinline__ void pass64(float (&acc)[64], uint32_t xlo, bool lane0, Side side) {
#pragma unroll
  for (int hs = HS0; hs < 14; hs++) {
    const int st = hs >> 1, k = (hs & 1) * 2;
    const int slot = (IT0 + st) % NSLOT, ph = ((IT0 + st) / NSLOT) & 1;
    const uint32_t a = xlo + st * 1024 + 2 * k, b = desc_lo(OFF_RING + slot * 16384, 8192) + 128 * k;
    if (!(hs & 1)) mbar_wait(B_FULL + 8 * slot, ph);
    wg_fence();
    mma_n128(acc, a, b, DESC_HI, hs != 0);
    mma_n128(acc, a + 2, b + 128, DESC_HI, 1);
    wg_commit();
    sched_fence();
    side(hs);
    sched_fence();
    wg_wait<0>();
    if (hs & 1) mbar_arrive_if(lane0, B_EMPTY + 8 * slot);
  }
  reg_fence(acc);
}

template <int IT0, class Side>
__device__ __forceinline__ void pass32(float (&acc)[32], uint32_t xlo, bool lane0, Side side) {
#pragma unroll
  for (int hs = 0; hs < 7; hs++) {
    const int st = hs >> 1;
    const int slot = (IT0 + st) % NSLOT, ph = ((IT0 + st) / NSLOT) & 1;
    const uint32_t a = xlo + hs * 1024, b = desc_lo(OFF_RING + slot * 16384, 4096) + (hs & 1) * 512;
    if (!(hs & 1)) mbar_wait(B_FULL + 8 * slot, ph);
    wg_fence();
#pragma unroll
    for (int k = 0; k < 4; k++) mma_ss64(acc, a + 2 * k, b + 64 * k, DESC_HI64, (hs | k) != 0);
    wg_commit();
    sched_fence();
    side(hs);
    sched_fence();
    wg_wait<0>();
    if ((hs & 1) || hs == 6) mbar_arrive_if(lane0, B_EMPTY + 8 * slot);
  }
  reg_fence(acc);
}

struct Ring {
  uint32_t slot, phase;
  __device__ __forceinline__ void next() {
    if (++slot == NSLOT) { slot = 0; phase ^= 1; }
  }
};

__global__ void __launch_bounds__(512, 1)
fused_kernel(const __grid_constant__ Maps maps, const uint8_t* __restrict__ x, const __nv_bfloat16* __restrict__ gate_w,
             __nv_bfloat16* __restrict__ out) {
  const int warp = __shfl_sync(~0u, (int)(threadIdx.x >> 5), 0);
  const int wg = warp >> 2;
  const int lane = threadIdx.x & 31;
  const int m = blockIdx.x >> 3, j = blockIdx.x & 7;

  if (warp == 12) {
    if (elect_one()) {
      TS(0);
#pragma unroll
      for (int i = 0; i < 4 + NSLOT; i++) mbar_init(B_EFULL + 8 * i, 1);
#pragma unroll
      for (int c = 0; c < XT; c++) mbar_init(B_XFULL + 8 * c, 1);
      TS(40);
#pragma unroll
      for (int s = 0; s < 4; s++) {
        if (!(s & 1) && s < 2 * XT) {
          mbar_expect_tx(B_XFULL + 4 * s, 16384);
          tma2d(OFF_X + s * 8192, &maps.x, s * 32, m * 128, B_XFULL + 4 * s);
        }
        mbar_expect_tx(B_EFULL + 8 * s, QKV_STAGE_BYTES);
        tma3d(OFF_E + s * 12288, &maps.qkv, 56 * j, 32 * s, 0, B_EFULL + 8 * s);
      }
      TS(42);
    }
  } else if (warp == 13) {
    if (elect_one()) {
      if (smem_u32(smem_raw) != SB) __trap();
#pragma unroll
      for (uint32_t b = B_KVFULL; b < B_EMPTY; b += 8) mbar_init(b, 1);
    }
  } else if (warp == 15) {
    if (elect_one()) {
#pragma unroll
      for (uint32_t b = B_EMPTY; b < B_END; b += 8)
        if (b < B_XFULL || b >= B_XFULL + 8 * XT) mbar_init(b, b < B_XFULL ? 8 : 4);
    }
  } else if (warp == 14) {
    const uint8_t* gw = reinterpret_cast<const uint8_t*>(gate_w) + lane * 16;
    asm volatile("cp.async.cg.shared.global [%0], [%1], 16;" ::"r"(OFF_GW + lane * 16), "l"(gw) : "memory");
    if (lane < 24) asm volatile("cp.async.cg.shared.global [%0], [%1], 16;" ::"r"(OFF_GW + 512 + lane * 16), "l"(gw + 512) : "memory");
    if (lane == 31) asm volatile("cp.async.cg.shared.global [%0], [%1], 16;" ::"r"(OFF_EPOCH + 16), "l"(&g_ex[blockIdx.x].flag) : "memory");
    if (elect_one()) prefetch_map(&maps.qkv);
  }
  __syncthreads();

  if (wg == 3) {
    if (warp == 12) {
      if (elect_one()) {
#pragma unroll 1
        for (int s = 4; s < 8; s++) {
          mbar_expect_tx(B_FULL + 8 * (s - 4), QKV_STAGE_BYTES);
          tma3d(OFF_RING + (s - 4) * 16384, &maps.qkv, 56 * j, 32 * s, 0, B_FULL + 8 * (s - 4));
        }
      }
    } else if (warp == 14) {
      asm volatile("cp.async.wait_all;" ::: "memory");
      __syncwarp();
      unsigned short v[8];
#pragma unroll
      for (int s = 0; s < 8; s++) asm volatile("ld.shared.u16 %0, [%1];" : "=h"(v[s]) : "r"(OFF_GW + s * 64 + lane * 2) : "memory");
      sts32(OFF_EPOCH, __float_as_uint(lds_f32(OFF_EPOCH + 20)) + 1);
#pragma unroll
      for (int s = 0; s < 8; s++) {
        const uint32_t buf = (s & 4) ? OFF_RING + (s & 3) * 16384 : OFF_E + (s & 3) * 12288;
        asm volatile("st.shared.u16 [%0], %1;" ::"r"(buf + lane * 128 + ((7 ^ (lane & 7)) << 4)), "h"(v[s]) : "memory");
      }
      fence_async_smem();
      __syncwarp();
      mbar_arrive_if(lane == 0, B_GW);
    }
    __syncwarp();
    asm volatile("setmaxnreg.dec.sync.aligned.u32 24;");
    if (warp == 12) {
      if (!elect_one()) return;
      const int f0 = 224 * j;
      const int fh = (j & 1) ? f0 : f0 + 192;
      const int ff = (j & 1) ? f0 + 32 : f0;
      Ring r{0, 0};
#pragma unroll 1
      for (int s = 8; s < 14; s++) {
        if (s & 4) {
          mbar_wait(B_EMPTY + 8 * r.slot, r.phase);
          mbar_expect_tx(B_FULL + 8 * r.slot, QKV_STAGE_BYTES);
          tma3d(OFF_RING + r.slot * 16384, &maps.qkv, 56 * j, 32 * s, 0, B_FULL + 8 * r.slot);
          r.next();
        } else {
          const int e = s & 3;
          mbar_wait(B_EEMPTY + 8 * e, 0);
          mbar_expect_tx(B_EFULL + 8 * e, QKV_STAGE_BYTES);
          tma3d(OFF_E + e * 12288, &maps.qkv, 56 * j, 32 * s, 0, B_EFULL + 8 * e);
        }
      }
#pragma unroll 1
      for (int ps = 0; ps < 3; ps++) {
        if (ps == 2) {
#pragma unroll 1
          for (int s = 0; s < 4; s++) {
            const uint32_t fb = B_FULL + 8 * r.slot, dst = OFF_RING + r.slot * 16384;
            mbar_wait(B_EMPTY + 8 * r.slot, r.phase);
            mbar_expect_tx(fb, s < 3 ? 16384 : 8192);
            tma2d(dst, &maps.g32, fh, 128 * s, fb);
            tma2d(dst + 4096, &maps.u32, fh, 128 * s, fb);
            if (s < 3) {
              tma2d(dst + 8192, &maps.g32, fh, 128 * s + 64, fb);
              tma2d(dst + 12288, &maps.u32, fh, 128 * s + 64, fb);
            }
            r.next();
          }
        }
#pragma unroll 1
        for (int s = 0; s < 7; s++) {
          const uint32_t fb = B_FULL + 8 * r.slot, dst = OFF_RING + r.slot * 16384;
          mbar_wait(B_EMPTY + 8 * r.slot, r.phase);
          mbar_expect_tx(fb, 16384);
          tma2d(dst, &maps.g64, ff + 64 * ps, 64 * s, fb);
          tma2d(dst + 8192, &maps.u64, ff + 64 * ps, 64 * s, fb);
          r.next();
        }
      }
      uint32_t gb = 0;
#pragma unroll 1
      for (int c = 0; c < 7; c++) {
        if (c >= 3) {
          mbar_wait(B_GEMPTY + 8 * gb, c >= 6);
        } else if (c > 0) {
#pragma unroll 1
          for (int i = 0; i < 2; i++) {
            mbar_wait(B_EMPTY + 8 * r.slot, r.phase);
            r.next();
          }
          if (c == 2) mbar_arrive(B_GO);
        }
        const uint32_t fb = B_GFULL + 8 * gb, dst = g2_buf(gb);
        mbar_expect_tx(fb, G2_BYTES);
        tma2d(dst, &maps.down64, 64 * c, ff, fb);
        tma2d(dst + 8192, &maps.down64, 64 * c, ff + 64, fb);
        tma2d(dst + 16384, &maps.down, 64 * c, fh, fb);
        tma2d(dst + 20480, &maps.down64, 64 * c, ff + 128, fb);
        tma2d(dst + 28672, &maps.wo, 64 * c, 56 * j, fb);
        gb = gb == 2 ? 0 : gb + 1;
      }
    } else if (warp == 13) {
      const uint32_t b = blockIdx.x;
      mbar_wait(B_GW, 0);
      const unsigned epoch = __float_as_uint(lds_f32(OFF_EPOCH));
      const int back = lane < 2 ? lane + 1 : 0;
      const unsigned* flag = &g_ex[m >= back ? b - 8 * back : b].flag;
      const int nB = min(5, 2 * m + 2), nsteps = nB + min(5, 2 * m + 1);
      auto key_block = [&](int n) { return n < nB ? 2 * m + 1 - (nB == 5 && n >= 3 ? 7 - n : n) : 2 * m + nB - n; };
      mbar_wait(B_K1RDY, 0);
      const int settle = epoch == 1 ? 1 : min(5, nsteps);
#pragma unroll 1
      for (int n = 1; n <= nsteps; n++) {
        if (n == settle) {
          if (lane < 3) flag_wait(flag, epoch * 8 + 5);
          __syncwarp();
          fence_async_global();
          mbar_arrive_if(lane == 0, B_SETTLED);
        }
        if (n == nsteps) break;
        const int kv = key_block(n), kk = key_block(n + 1);
        const uint32_t fb = B_KVFULL + 8 * (n & 1);
        if (n < settle) {
          const int need = lane == 0 ? (m >= 2 || n == 1 ? n : min(n + 1, 4)) : (m >= 2 && n < 4 ? n - 1 : 0);
          if (lane < 2 && need) flag_wait(flag, epoch * 8 + need);
          if (n < 4) mbar_wait(B_PUB + 8 * (m > 0 ? n - 1 : 2), 0);
          __syncwarp();
          if (n < 3) TS(22 + n);
        }
        mbar_wait(B_KVEMPTY + 8 * ((n - 1) & 1), ((n - 1) >> 1) & 1);
        if (elect_one()) {
          mbar_expect_tx(fb, (n == 1 || n + 1 == nsteps) ? 8192 : 16384);
          if (n + 1 < nsteps) bulk_load(OFF_KV + ((n + 1) & 1) * 16384, kv_block(kk, j), 8192, fb);
          if (n > 1) bulk_load(OFF_KV + (n & 1) * 16384 + 8192, kv_block(kv, j) + 8192, 8192, fb);
        }
      }
    } else {
      if (warp == 14) {
        if (elect_one()) {
          *(volatile unsigned*)&g_ex[blockIdx.x].epoch = __float_as_uint(lds_f32(OFF_EPOCH));
          prefetch_map(&maps.g64);
          prefetch_map(&maps.u64);
          prefetch_map(&maps.g32);
          prefetch_map(&maps.u32);
          prefetch_map(&maps.down);
          prefetch_map(&maps.down64);
          prefetch_map(&maps.wo);
          prefetch_map(&maps.out);
        }
        __syncwarp();
#pragma unroll 1
        for (int s = 8; s < 14; s++) {
          unsigned short v;
          asm volatile("ld.shared.u16 %0, [%1];" : "=h"(v) : "r"(OFF_GW + s * 64 + lane * 2) : "memory");
          mbar_wait((s & 4) ? B_EMPTY + 8 * (s & 3) : B_EEMPTY + 8 * (s & 3), 0);
          const uint32_t buf = (s & 4) ? OFF_RING + (s & 3) * 16384 : OFF_E + (s & 3) * 12288;
          asm volatile("st.shared.u16 [%0], %1;" ::"r"(buf + lane * 128 + ((7 ^ (lane & 7)) << 4)), "h"(v) : "memory");
          fence_async_smem();
          __syncwarp();
          mbar_arrive_if(lane == 0, B_GW + 8 * (s - 7));
        }
        return;
      }
      if (!elect_one()) return;
      mbar_wait(B_GW, 0);
      const unsigned epoch = __float_as_uint(lds_f32(OFF_EPOCH));
#pragma unroll 1
      for (int i = 0; i < 4; i++) {
        mbar_wait(i == 0 ? B_K1RDY : B_VRDY, 0);
        uint8_t* dst = g_ex[blockIdx.x].kv[1 - (i >> 1)] + (i & 1) * 8192;
        asm volatile("cp.async.bulk.global.shared::cta.bulk_group [%0], [%1], 8192;" ::"l"(dst), "r"(OFF_KV + i * 8192) : "memory");
        asm volatile("cp.async.bulk.commit_group;" ::: "memory");
        asm volatile("cp.async.bulk.wait_group 0;" ::: "memory");
        asm volatile("st.relaxed.gpu.global.u32 [%0], %1;" ::"l"(&g_ex[blockIdx.x].flag), "r"(epoch * 8 + 1 + i) : "memory");
        if (i != 1) mbar_arrive(B_PUB + 8 * (i == 0 ? 0 : i - 1));
        if (i == 0) TS(25);
      }
      asm volatile("st.release.gpu.global.u32 [%0], %1;" ::"l"(&g_ex[blockIdx.x].flag), "r"(epoch * 8 + 5) : "memory");
      TS(26);
      mbar_wait(B_ZRDY, 0);
      asm volatile("red.release.gpu.global.add.u32 [%0], 1;" ::"l"(&g_zflag[m * 8]) : "memory");
      flag_wait(&g_zflag[m * 8], epoch * 8);
      mbar_arrive(B_ZOK);
    }
  } else if (wg == 2) {
    const int t = threadIdx.x & 127;
    const bool lane0 = lane == 0;
    {
      const uint32_t r0 = t >> 3, ch = t & 7;
      const uint8_t* src = x + (size_t)(m * 128 + r0) * 896 + ch * 16;
      const uint32_t dst = OFF_X + r0 * 128 + ((ch ^ (r0 & 7)) << 4);
#pragma unroll 1
      for (int c = XT; c < 7 + XAHEAD; c++) {
        if (c < 7) {
#pragma unroll
          for (int i = 0; i < 8; i++)
            asm volatile("cp.async.cg.shared.global [%0], [%1], 16;" ::"r"(dst + c * 16384 + i * 2048), "l"(src + c * 128 + i * 16 * 896) : "memory");
        }
        asm volatile("cp.async.commit_group;" ::: "memory");
        if (c >= XT + XAHEAD) {
          asm volatile("cp.async.wait_group %0;" ::"n"(XAHEAD) : "memory");
          fence_async_smem();
          __syncwarp();
          mbar_arrive_if(lane0, B_XFULL + 8 * (c - XAHEAD));
          TS(33 + c - XAHEAD);
        }
      }
      uint4* z = reinterpret_cast<uint4*>(out + (size_t)(m * 128 + j * 16) * 448);
#pragma unroll
      for (int i = 0; i < 7; i++) z[t + i * 128] = make_uint4(0, 0, 0, 0);
      __syncwarp();
      mbar_arrive_if(lane0, B_ZRDY);
    }
    asm volatile("setmaxnreg.inc.sync.aligned.u32 152;");
    const int wi = warp & 3, q = lane & 3;
    const int row = wi * 16 + (lane >> 2);
    constexpr uint32_t QLO = desc_lo(OFF_QO, 16), KVLO = desc_lo(OFF_KV, 16);
    float sa[32], sb[32], o0[16], o1[16];
    uint32_t p[16];
    bool odd = false;
    float g0 = 0.f, g1 = 0.f;
    auto load_gate = [&](int w) {
      g0 = lds_f32(OFF_G + (w * 64 + row) * 4);
      g1 = lds_f32(OFF_G + (w * 64 + row + 8) * 4);
    };
    auto finalize = [&](int w, bool check) -> bool {
      const float l00 = __shfl_sync(~0u, odd ? o0[5] : o0[4], lane | 3), l01 = __shfl_sync(~0u, odd ? o0[7] : o0[6], lane | 3);
      const float l10 = __shfl_sync(~0u, odd ? o1[13] : o1[12], lane & ~3), l11 = __shfl_sync(~0u, odd ? o1[15] : o1[14], lane & ~3);
      if (check) {
        uint32_t d[4];
#pragma unroll
        for (int i = 0; i < 4; i++) {
          const float* o = (i < 2 ? o0 : o1) + 4 + 8 * (i & 1);
          const uint32_t e = __float_as_uint(o[0]) | __float_as_uint(o[2]), f = __float_as_uint(o[1]) | __float_as_uint(o[3]);
          d[i] = odd ? e : f;
        }
        const uint32_t da = (q & 1) ? d[0] : d[1], db = (q & 1) ? d[2] : d[3];
        const uint32_t dd = (q & 2) ? da : db;
        const float lo = fminf(fminf(l00, l01), fminf(l10, l11)), hi = l00 + l01 + l10 + l11;
        if (!__all_sync(~0u, (dd << 1) == 0 && lo >= 0x1p-100f && hi <= 0x1p100f)) return false;
      }
      const float i00 = g0 * rcp_fast(l00), i01 = g1 * rcp_fast(l01);
      const float i10 = g0 * rcp_fast(l10), i11 = g1 * rcp_fast(l11);
      uint32_t v[16];
#pragma unroll
      for (int g = 0; g < 4; g++) {
        v[2 * g] = pack_bf16(o0[4 * g] * i00, o0[4 * g + 1] * i00);
        v[2 * g + 1] = pack_bf16(o0[4 * g + 2] * i01, o0[4 * g + 3] * i01);
        v[8 + 2 * g] = pack_bf16(o1[4 * g] * i10, o1[4 * g + 1] * i10);
        v[8 + 2 * g + 1] = pack_bf16(o1[4 * g + 2] * i11, o1[4 * g + 3] * i11);
      }
#pragma unroll
      for (int g = 0; g < 4; g++) sts128(OFF_QO + w * 8192 + wi * 2048 + g * 512 + lane * 16, v[4 * g], v[4 * g + 1], v[4 * g + 2], v[4 * g + 3]);
      __syncwarp();
      mbar_arrive_if(lane0, B_ORDY + 8 * w);
      TS(31 + w);
      return true;
    };
    const uint32_t tri = ((2 * q <= (lane >> 2)) ? 0xffffu : 0u) | ((2 * q + 1 <= (lane >> 2)) ? 0xffff0000u : 0u);
    PMask mk;
#pragma unroll
    for (int k = 0; k < 4; k++) {
      mk.d[k] = k == wi ? tri : (k < wi ? ~0u : 0u);
      asm volatile("" : "+r"(mk.d[k]));
      if (k < 3) {
        mk.t[k] = k < wi ? ~0u : 0u;
        asm volatile("" : "+r"(mk.t[k]));
      }
    }
#pragma unroll
    for (int i = 0; i < 16; i++) p[i] = 0u;
    mbar_wait(B_QKRDY + 8, 0);
    odd = __float_as_uint(lds_f32(OFF_EPOCH)) & 1;
    TS(30);
    issue_s(sa, QLO + 512, KVLO);
    wg_wait<0>();
    reg_fence(sa);
    uint32_t ctl = m >= 2 ? 012000142001u : (m == 1 ? 010014001u : 01141u);
    asm volatile("" : "+r"(ctl));
    uint32_t qd = QLO + 512;
    uint32_t kd = KVLO, kp = KVLO - 512;
    int acc_prev = 0;
    uint32_t redo = 0;
    uint32_t gbar = B_VRDY, gpar = 0, ebar = B_KVEMPTY;
    int n = 0;
#pragma unroll 1
    do {
      TA(0);
      issue_s_pv(sb, qd + 4, kd + 4, o1, p, kp + 512 + 4, acc_prev);
      TA(1);
      ex2_groups<0, GX>(sa);
      reg_fence(sa);
      const uint32_t landed = mbar_try(gbar, gpar);
      uint32_t qn = (ctl & 4) ? QLO : qd;
      uint32_t kn = (ctl >> 3) != 1 ? kd ^ 1024 : kd + 512;
      uint32_t inv = (ctl & 2) ? ~0u : 0u;
      acc_prev = !(ctl & 1);
      asm volatile("" : "+r"(qn), "+r"(kn), "+r"(inv), "+r"(acc_prev));
      sched_fence();
      TA(2);
      wg_wait<0>();
      TA(3);
      reg_fence(o1);
      reg_fence(p);
      reg_fence(sb);
      mbar_arrive_if(lane0, ebar);
      ex2_groups<GX, 8>(sa);
      pack_p(sa, p);
      if (ctl & 3) {
        mask_p(p, mk, inv);
        if ((ctl & 1) && qd == QLO && !finalize(1, true)) redo = 2;
      }
      TA(4);
      if (!landed) mbar_wait(gbar, gpar);
      TA(5);
      issue_s_pv(sa, qn, kn, o0, p, kd + 512, acc_prev);
      TA(6);
      ex2_groups<0, GX>(sb);
      reg_fence(sb);
      gbar = B_KVFULL + 8 * ((n + 1) & 1);
      gpar = (n >> 1) & 1;
      ebar ^= 8;
      kp = kd;
      kd ^= 1024;
      asm volatile("" : "+r"(gbar), "+r"(gpar), "+r"(ebar), "+r"(kp), "+r"(kd));
      sched_fence();
      wg_wait<0>();
      sched_fence();
      TA(7);
      reg_fence(o0);
      reg_fence(p);
      reg_fence(sa);
      ex2_groups<GX, 8>(sb);
      pack_p(sb, p);
      if (ctl & 3) {
        mask_p(p, mk, inv);
        if (ctl & 1) load_gate(qd != QLO);
      }
      qd = qn;
      ctl >>= 3;
      TS(44 + n);
      n++;
    } while (ctl != 1);
    issue_pv(o1, p, kp + 512 + 4, acc_prev);
    wg_wait<0>();
    reg_fence(o1);
    reg_fence(p);
    if (!finalize(0, true)) redo |= 1;
    uint32_t any;
    asm volatile("{\n.reg .pred p, q;\nsetp.ne.u32 p, %1, 0;\nbar.red.or.pred q, 1, 128, p;\nselp.u32 %0, 1, 0, q;\n}"
                 : "=r"(any) : "r"(redo) : "memory");
    if (any) {
      uint32_t ph = 0;
      RowStat r0{}, r1{};
      mbar_wait(B_SETTLED, 0);
#pragma unroll 1
      for (int w = 0; w < 2; w++) {
        const int cnt = min(5, 2 * m + 1 + w);
#pragma unroll 1
        for (int t = 0; t < cnt; t++) {
          asm volatile("bar.sync 1, 128;" ::: "memory");
          if (wi == 0 && elect_one()) {
            fence_async_global();
            mbar_expect_tx(B_SLOW, 16384);
            bulk_load(OFF_KV, kv_block(2 * m + w - t, j), 16384, B_SLOW);
          }
          mbar_wait(B_SLOW, ph);
          ph ^= 1;
          auto head = [&](float (&o)[16], RowStat& r, uint32_t hoff) {
            issue_s(sa, QLO + w * 512 + hoff, KVLO + hoff);
            wg_wait<0>();
            reg_fence(sa);
            if ((t & 3) == 0) mask_block(sa, t == 0, row, q);
            update_max(sa, r, t == 0);
            exp_shifted(sa, r.m0, r.m1);
            pack_p(sa, p);
#pragma unroll
            for (int g = 0; g < 4; g++) {
              o[4 * g] *= r.al0; o[4 * g + 1] *= r.al0; o[4 * g + 2] *= r.al1; o[4 * g + 3] *= r.al1;
            }
            issue_pv(o, p, KVLO + 512 + hoff, t != 0);
            wg_wait<0>();
            reg_fence(o);
            reg_fence(p);
          };
          head(o0, r0, 0);
          head(o1, r1, 4);
        }
        if ((redo >> w) & 1) {
          load_gate(w);
          finalize(w, false);
        }
      }
    }
  } else {
    const int w = wg, wi = warp & 3, q = lane & 3;
    const bool lane0 = lane == 0;
    const int row = wi * 16 + (lane >> 2);
    const uint32_t xlo = desc_lo(OFF_X, 16) + w * 512;
    float acc[92];
    uint32_t vp[14], sh;
    const uint32_t srow = (wi * 16 + (lane & 7) + ((lane >> 3) & 1) * 8) * 128;
    {
      uint32_t prev = 0;
#pragma unroll 1
      for (int s = 0; s < 14; s++) {
        if (!(s & 1)) mbar_wait(B_XFULL + 4 * s, 0);
        const bool ring = s & 4;
        const uint32_t sl = s & 3;
        const uint32_t a = xlo + (s >> 1) * 1024 + (s & 1) * 4;
        const uint32_t b = ring ? desc_lo(OFF_RING, 4096) + sl * 1024 : desc_lo(OFF_E, 4096) + sl * 768;
        if (s == 0 || s >= 8) mbar_wait(B_GW + 8 * max(s - 7, 0), 0);
        mbar_wait((ring ? B_FULL : B_EFULL) + 8 * sl, s >> 3);
        if (s == 0) TS(1 + w);
        wg_fence();
        mma_qkv(acc, a, b, DESC_HI, s);
        mma_qkv(acc, a + 2, b + 128, DESC_HI, 1);
        wg_commit();
        wg_wait<1>();
        mbar_arrive_if(lane0 && s > 0, prev);
        prev = (ring ? B_EMPTY : B_EEMPTY) + 8 * sl;
      }
      sh = (__float_as_uint(lds_f32(OFF_EPOCH)) & 1) * 16;
      mbar_wait(B_EEMPTY + 8 * 3, 1);
      wg_wait<0>();
      mbar_arrive_if(lane0, prev);
      reg_fence(acc);
      TS(3 + w);
    }
    uint32_t h[72];
    float a0, a1;
    float accA[64], accB[64], accH[32], accC[64];
    {
      const uint32_t kvt = OFF_KV + (1 - w) * 16384 + srow;
#pragma unroll
      for (int i = 0; i < 14; i++) vp[i] = pack_bf16(acc[64 + 2 * i], acc[64 + 2 * i + 1]);
      reg_fence(vp);
      asm volatile("setmaxnreg.inc.sync.aligned.u32 168;");
      mbar_wait(B_FULL + 8 * ((IT_P1 + 0) % NSLOT), ((IT_P1 + 0) / NSLOT) & 1);
      wg_fence();
#pragma unroll
      for (int k = 0; k < 4; k++)
        mma_n128(accA, xlo + 0 * 1024 + 2 * k, desc_lo(OFF_RING + ((IT_P1 + 0) % NSLOT) * 16384, 8192) + 128 * k, DESC_HI, k != 0);
      wg_commit();
      sched_fence();
      {
        uint32_t v[14];
#pragma unroll
        for (int i = 0; i < 14; i++) v[i] = pack_bf16(acc[32 + 2 * i], acc[32 + 2 * i + 1]);
        store_heads(kvt, lane, v, 0x3F80u << sh);
        if (w == 1) {
          fence_async_smem();
          __syncwarp();
          mbar_arrive_if(lane0, B_K1RDY);
        }
      }
      mbar_wait(B_FULL + 8 * ((IT_P1 + 1) % NSLOT), ((IT_P1 + 1) / NSLOT) & 1);
      wg_fence();
#pragma unroll
      for (int k = 0; k < 4; k++)
        mma_n128(accA, xlo + 1 * 1024 + 2 * k, desc_lo(OFF_RING + ((IT_P1 + 1) % NSLOT) * 16384, 8192) + 128 * k, DESC_HI, 1);
      wg_commit();
      wg_wait<1>();
      mbar_arrive_if(lane0, B_EMPTY + 8 * ((IT_P1 + 1 - 1) % NSLOT));
      sched_fence();
      {
        uint32_t v[14];
#pragma unroll
        for (int i = 0; i < 14; i++) v[i] = pack_bf16(acc[2 * i] * SM_C, acc[2 * i + 1] * SM_C);
        store_heads(OFF_QO + w * 8192 + srow, lane, v, 0x71800000u >> sh);
      }
      fence_async_smem();
      __syncwarp();
      mbar_arrive_if(lane0, B_QKRDY + 8 * w);
      TS(5 + w);
      mbar_wait(B_FULL + 8 * ((IT_P1 + 2) % NSLOT), ((IT_P1 + 2) / NSLOT) & 1);
      wg_fence();
#pragma unroll
      for (int k = 0; k < 4; k++)
        mma_n128(accA, xlo + 2 * 1024 + 2 * k, desc_lo(OFF_RING + ((IT_P1 + 2) % NSLOT) * 16384, 8192) + 128 * k, DESC_HI, 1);
      wg_commit();
      wg_wait<1>();
      mbar_arrive_if(lane0, B_EMPTY + 8 * ((IT_P1 + 2 - 1) % NSLOT));
      sched_fence();
      uint32_t big = 0;
#pragma unroll
      for (int i = 0; i < 14; i += 2) big = __vimax3_u16x2(big, vp[i] & 0x7fff7fffu, vp[i + 1] & 0x7fff7fffu);
      const bool huge = __any_sync(~0u, max(big >> 16, big & 0xffffu) >= 0x4980u);
      store_heads(kvt + 8192, lane, vp, huge ? 0x3F803F80u : 0x3F80u << sh);
      const float g0 = __fdividef(1.f, 1.f + __expf(-__shfl_sync(~0u, acc[28], lane & ~3)));
      const float g1 = __fdividef(1.f, 1.f + __expf(-__shfl_sync(~0u, acc[30], lane & ~3)));
      sts32(OFF_G + (w * 64 + row + (q & 1) * 8) * 4, __float_as_uint((q & 1) ? g1 : g0));
      a0 = 0.5f - 0.5f * g0;
      a1 = 0.5f - 0.5f * g1;
      fence_async_smem();
      __syncwarp();
      mbar_arrive_if(lane0, B_VRDY);
      TS(27 + w);
      sched_fence();
      wg_wait<0>();
      mbar_arrive_if(lane0, B_EMPTY + 8 * ((IT_P1 + 2) % NSLOT));
    }
    pass64<IT_P1, 6>(accA, xlo, lane0, [](int) {});
    TS(7 + w);
    pass64<IT_P2, 0>(accB, xlo, lane0, [&](int hs) { if (hs < 8) glu_group<8>(h, accA, hs, a0, a1); });
    TS(9 + w);
    pass32<IT_P3>(accH, xlo, lane0, [&](int hs) {
      glu_group<8>(h + 16, accB, hs, a0, a1);
      if (hs == 0) glu_group<8>(h + 16, accB, 7, a0, a1);
    });
    TS(11 + w);
    pass64<IT_P4, 0>(accC, xlo, lane0, [&](int hs) { if (hs < 4) glu_group<4>(h + 32, accH, hs, a0, a1); });
    TS(13 + w);
    {
      float acc0[32], acc1[32];
      const uint32_t slot0 = wi * 2048 + ((lane & 7) + ((lane >> 3) & 1) * 8) * 128;
      auto slot = [&](int g) { return slot0 + (((2 * g + (lane >> 4)) ^ (lane & 7)) << 4); };
      auto emit = [&](int c, uint32_t tile) {
        fence_async_smem();
        __syncwarp();
        if (elect_one()) {
          asm volatile("cp.reduce.async.bulk.tensor.2d.global.shared::cta.add.tile.bulk_group [%0, {%2, %3}], [%1];"
                       ::"l"(&maps.out), "r"(tile + wi * 2048), "r"(c * 64), "r"(m * 128 + w * 64 + wi * 16) : "memory");
          asm volatile("cp.async.bulk.commit_group;" ::: "memory");
        }
        __syncwarp();
      };
      auto mma_k = [&](float (&acc)[32], uint32_t b, int k) {
        mma_rs64(acc, h[4 * k], h[4 * k + 1], h[4 * k + 2], h[4 * k + 3], b + k * 128, DESC_HI, k);
      };
      {
        constexpr uint32_t b = desc_lo(g2_buf(0), 4096);
        mbar_wait(B_GFULL, 0);
        wg_fence();
#pragma unroll
        for (int k = 0; k < 6; k++) mma_k(acc0, b, k);
        wg_commit();
        sched_fence();
#pragma unroll
        for (int g = 0; g < 4; g++) glu_group<8>(h + 40, accC, g, a0, a1);
        wg_fence();
#pragma unroll
        for (int k = 6; k < 12; k++) mma_k(acc0, b, k);
        wg_commit();
        sched_fence();
#pragma unroll
        for (int g = 4; g < 8; g++) glu_group<8>(h + 40, accC, g, a0, a1);
        mbar_wait(B_ZOK, 0);
        fence_async_global();
        mbar_wait(B_GO, 0);
        mbar_wait(B_ORDY + 8 * w, 0);
        TS(15 + w);
#pragma unroll
        for (int g = 0; g < 4; g++) {
          const uint4 r = lds128(OFF_QO + w * 8192 + wi * 2048 + g * 512 + lane * 16);
          h[56 + 4 * g] = r.x; h[57 + 4 * g] = r.y; h[58 + 4 * g] = r.z; h[59 + 4 * g] = r.w;
        }
#pragma unroll
        for (int i = 2; i < 14; i++) h[56 + i] = q >= (8 - i / 2) / 2 ? h[58 + i] : h[56 + i];
        h[70] = h[71] = 0u;
        wg_fence();
#pragma unroll
        for (int k = 12; k < 18; k++) mma_k(acc0, b, k);
        wg_commit();
      }
      uint32_t gb = 1;
      auto chunk = [&](float (&acc)[32], float (&prv)[32], int c) {
        const uint32_t b = desc_lo(0, 4096) + (g2_buf(gb) >> 4), tile = out_tile(((c - 1) & 3) * 2 + w);
        mbar_wait(B_GFULL + 8 * gb, c >= 3 && c < 6);
        wg_fence();
#pragma unroll
        for (int k = 0; k < G2A; k++) mma_k(acc, b, k);
        wg_commit();
        wg_wait<1>();
        reg_fence(prv);
        mbar_arrive_if(lane0, B_GEMPTY + 8 * (gb == 0 ? 2 : gb - 1));
        if (c >= 5) {
          if (elect_one()) asm volatile("cp.async.bulk.wait_group.read 3;" ::: "memory");
          __syncwarp();
        }
#pragma unroll
        for (int g = 0; g < 4; g++)
          stsm4(tile + slot(g), pack_bf16(prv[8 * g], prv[8 * g + 1]), pack_bf16(prv[8 * g + 2], prv[8 * g + 3]),
                pack_bf16(prv[8 * g + 4], prv[8 * g + 5]), pack_bf16(prv[8 * g + 6], prv[8 * g + 7]));
        wg_fence();
#pragma unroll
        for (int k = G2A; k < G2B; k++) mma_k(acc, b, k);
        wg_commit();
        emit(c - 1, tile);
        wg_fence();
#pragma unroll
        for (int k = G2B; k < 18; k++) mma_k(acc, b, k);
        wg_commit();
        TS((w == 1 ? 53 : 70) + c);
        gb = gb == 2 ? 0 : gb + 1;
      };
#pragma unroll 1
      for (int c = 1; c < 7; c += 2) {
        chunk(acc1, acc0, c);
        chunk(acc0, acc1, c + 1);
      }
      wg_wait<0>();
      TS(17 + w);
      reg_fence(acc0);
#pragma unroll
      for (int g = 0; g < 4; g++)
        stsm4(OFF_QO + w * 8192 + slot(g), pack_bf16(acc0[8 * g], acc0[8 * g + 1]), pack_bf16(acc0[8 * g + 2], acc0[8 * g + 3]),
              pack_bf16(acc0[8 * g + 4], acc0[8 * g + 5]), pack_bf16(acc0[8 * g + 6], acc0[8 * g + 7]));
      emit(6, OFF_QO + w * 8192);
      if (elect_one()) asm volatile("cp.async.bulk.wait_group.read 0;" ::: "memory");
      TS(21 + w);
    }
  }
}

typedef CUresult (*EncodeFn)(CUtensorMap*, CUtensorMapDataType, cuuint32_t, void*, const cuuint64_t*, const cuuint64_t*,
                             const cuuint32_t*, const cuuint32_t*, CUtensorMapInterleave, CUtensorMapSwizzle,
                             CUtensorMapL2promotion, CUtensorMapFloatOOBfill);

void encode(EncodeFn fn, CUtensorMap* m, const void* p, int rank, const cuuint64_t* dims, const cuuint64_t* strides,
            const cuuint32_t* box, CUtensorMapSwizzle sw = CU_TENSOR_MAP_SWIZZLE_128B) {
  const cuuint32_t es[3] = {1, 1, 1};
  fn(m, CU_TENSOR_MAP_DATA_TYPE_BFLOAT16, rank, const_cast<void*>(p), dims, strides, box, es, CU_TENSOR_MAP_INTERLEAVE_NONE,
     sw, CU_TENSOR_MAP_L2_PROMOTION_L2_128B, CU_TENSOR_MAP_FLOAT_OOB_FILL_NONE);
}
void encode2d(EncodeFn fn, CUtensorMap* m, const void* p, uint64_t cols, uint64_t rows, uint32_t bc, uint32_t br,
              CUtensorMapSwizzle sw = CU_TENSOR_MAP_SWIZZLE_128B) {
  const cuuint64_t dims[2] = {cols, rows}, strides[1] = {cols * 2};
  const cuuint32_t box[2] = {bc, br};
  encode(fn, m, p, 2, dims, strides, box, sw);
}

}

extern "C" void kernel_launch(void* const* d_in, const int* in_sizes, int n_in, void* d_out, int out_size) {
  (void)in_sizes; (void)n_in; (void)out_size;
  void* fp = nullptr;
  cudaDriverEntryPointQueryResult qr;
  cudaGetDriverEntryPoint("cuTensorMapEncodeTiled", &fp, cudaEnableDefault, &qr);
  EncodeFn fn = (EncodeFn)fp;
  Maps maps;
  encode2d(fn, &maps.x, d_in[0], 448, 2048, 64, 128);
  {
    const cuuint64_t dims[3] = {448, 448, 3}, strides[2] = {1344 * 2, 448 * 2};
    const cuuint32_t box[3] = {56, 32, 3};
    encode(fn, &maps.qkv, d_in[1], 3, dims, strides, box);
  }
  encode2d(fn, &maps.g64, d_in[4], 1792, 448, 64, 64);
  encode2d(fn, &maps.g32, d_in[4], 1792, 448, 32, 64, CU_TENSOR_MAP_SWIZZLE_64B);
  encode2d(fn, &maps.u64, d_in[5], 1792, 448, 64, 64);
  encode2d(fn, &maps.u32, d_in[5], 1792, 448, 32, 64, CU_TENSOR_MAP_SWIZZLE_64B);
  encode2d(fn, &maps.down, d_in[6], 448, 1792, 64, 32);
  encode2d(fn, &maps.down64, d_in[6], 448, 1792, 64, 64);
  encode2d(fn, &maps.wo, d_in[2], 448, 448, 64, 64);
  encode2d(fn, &maps.out, d_out, 448, 2048, 64, 16);
  cudaFuncSetAttribute(fused_kernel, cudaFuncAttributeMaxDynamicSharedMemorySize, SMEM_BYTES);
  fused_kernel<<<128, 512, SMEM_BYTES>>>(maps, (const uint8_t*)d_in[0], (const __nv_bfloat16*)d_in[7], (__nv_bfloat16*)d_out);
}
```

```cpp
#include <cuda_runtime.h>
#include <cuda_bf16.h>
#include <cuda.h>
#include <stdint.h>

namespace {

constexpr int NSLOT = 4;
constexpr int XAHEAD = 2;
constexpr uint32_t SB = 0x400;
constexpr uint32_t OFF_X = SB;
constexpr uint32_t OFF_QO = OFF_X + 114688;
constexpr uint32_t OFF_KV = OFF_QO + 16384;
constexpr uint32_t OFF_E = OFF_QO;
constexpr uint32_t OFF_RING = OFF_KV + 32768;
constexpr uint32_t OFF_BAR = OFF_RING + NSLOT * 16384;
constexpr uint32_t OFF_G = OFF_BAR + 768;
constexpr uint32_t OFF_EPOCH = OFF_G + 512;
constexpr uint32_t OFF_GW = OFF_EPOCH + 32;
constexpr uint32_t OFF_TS = OFF_GW + 896;
constexpr uint32_t SMEM_BYTES = OFF_TS + 384 - SB;

constexpr uint32_t B_EFULL = OFF_BAR;
constexpr uint32_t B_FULL = B_EFULL + 8 * 4;
constexpr uint32_t B_KVFULL = B_FULL + 8 * NSLOT;
constexpr uint32_t B_ZOK = B_KVFULL + 8 * 2;
constexpr uint32_t B_SLOW = B_ZOK + 8;
constexpr uint32_t B_SETTLED = B_SLOW + 8;
constexpr uint32_t B_PUB = B_SETTLED + 8;
constexpr uint32_t B_GW = B_PUB + 8 * 3;
constexpr uint32_t B_GFULL = B_GW + 8 * 7;
constexpr uint32_t B_GO = B_GFULL + 8 * 3;
constexpr uint32_t B_LFULL = B_GO + 8 * 2;
constexpr uint32_t B_PAD0 = B_LFULL + 8 * 6;
constexpr uint32_t B_PAD1 = B_PAD0 + 8;
constexpr uint32_t B_EPOCH = B_PAD1 + 8;
constexpr uint32_t B_EMPTY = B_EPOCH + 8;
constexpr uint32_t B_EEMPTY = B_EMPTY + 8 * NSLOT;
constexpr uint32_t B_GEMPTY = B_EEMPTY + 8 * 4;
constexpr uint32_t B_VRDY = B_GEMPTY + 8 * 3;
constexpr uint32_t B_GRDY = B_VRDY + 8;
constexpr uint32_t B_RCVD = B_GRDY + 8;
constexpr uint32_t B_XFULL = B_RCVD + 8;
constexpr uint32_t B_KVEMPTY = B_XFULL + 8 * 7;
constexpr uint32_t B_QKRDY = B_KVEMPTY + 8 * 2;
constexpr uint32_t B_ORDY = B_QKRDY + 8 * 2;
constexpr uint32_t B_ZRDY = B_ORDY + 8 * 2;
constexpr uint32_t B_K1RDY = B_ZRDY + 8;
constexpr uint32_t B_ATTDONE = B_K1RDY + 8;
constexpr uint32_t B_OUT = B_ATTDONE + 8;
constexpr uint32_t B_END = B_OUT + 8 * 14;
static_assert(B_KVEMPTY % 16 == 0, "toggled with ^ 8");
static_assert(B_END <= OFF_G, "barriers overflow");

constexpr uint32_t DESC_HI = 0x40000040u;
constexpr uint32_t DESC_HI64 = 0x80000020u;
constexpr uint32_t SPIN_LIMIT = 1u << 22;
constexpr uint32_t QKV_STAGE_BYTES = 3 * 32 * 112;

constexpr int IT_P1 = 6, IT_P2 = 13, IT_P3 = 20, IT_P4 = 24;
constexpr uint32_t G2_BYTES = 36864;
constexpr int G2A = 4, G2B = 9;
__host__ __device__ constexpr uint32_t g2_buf(uint32_t i) { return i < 2 ? OFF_X + i * G2_BYTES : OFF_RING; }
__host__ __device__ constexpr uint32_t out_tile(uint32_t i) { return i < 5 ? OFF_X + 73728 + i * 8192 : OFF_RING + i * 8192; }

__device__ __forceinline__ int g2_col(int p, int rank) {
  return 64 * (p == 1 ? 6 : ((p & 1) || p == 6 ? 3 - 3 * rank + (p >> 1) - 1 : 3 * rank + (p >> 1)));
}

__device__ __forceinline__ uint32_t g2_tile(int p, int w) {
  return p == 1 ? OFF_QO + w * 8192
                : ((p & 1) || p == 6 ? out_tile(2 * ((p >> 1) - 1) + w) : (p == 0 ? out_tile(6) : OFF_KV + (p - 2) * 8192) + w * 8192);
}

struct alignas(64) Maps {
  CUtensorMap qkv, g64, g32, u64, u32, down, down64, wo, out;
};

struct alignas(128) Exchange {
  uint8_t kv[2][16384];
  unsigned flag, epoch, pad[2];
};
__device__ Exchange g_ex[128];
__device__ unsigned g_zflag[16 * 8];
__device__ __forceinline__ const uint8_t* kv_block(int kb, int j) { return g_ex[(kb >> 1) * 8 + j].kv[kb & 1]; }
#define TS(i)
#define TA(i)

__device__ __forceinline__ uint32_t smem_u32(const void* p) { return (uint32_t)__cvta_generic_to_shared(p); }
extern __shared__ __align__(1024) uint8_t smem_raw[];
__device__ __forceinline__ uint32_t self(uint32_t a) { return a + (smem_u32(smem_raw) - SB); }
__device__ __forceinline__ uint32_t in_cta(uint32_t a, uint32_t rank) {
  uint32_t r;
  asm("mapa.shared::cluster.u32 %0, %1, %2;" : "=r"(r) : "r"(self(a)), "r"(rank));
  return r;
}
__device__ __forceinline__ void mbar_init(uint32_t bar, uint32_t cnt) {
  asm volatile("mbarrier.init.shared::cta.b64 [%0], %1;" ::"r"(self(bar)), "r"(cnt) : "memory");
}
__device__ __forceinline__ void mbar_expect_tx(uint32_t bar, uint32_t bytes) {
  asm volatile("mbarrier.arrive.expect_tx.shared::cta.b64 _, [%0], %1;" ::"r"(self(bar)), "r"(bytes) : "memory");
}
__device__ __forceinline__ void mbar_arrive(uint32_t bar) {
  asm volatile("mbarrier.arrive.shared::cta.b64 _, [%0];" ::"r"(self(bar)) : "memory");
}
__device__ __forceinline__ void mbar_arrive_if(bool pred, uint32_t bar) {
  asm volatile("{\n.reg .pred p;\nsetp.ne.u32 p, %1, 0;\n@p mbarrier.arrive.shared::cta.b64 _, [%0];\n}" ::"r"(self(bar)), "r"((uint32_t)pred) : "memory");
}
__device__ __forceinline__ void mbar_wait(uint32_t bar, uint32_t parity) {
  asm volatile(
      "{\n.reg .pred p;\n.reg .u32 n;\n"
      "mbarrier.try_wait.parity.shared::cta.b64 p, [%0], %1;\n"
      "@p bra DONE;\n"
      "mov.u32 n, 0;\n"
      "LOOP:\n"
      "mbarrier.try_wait.parity.shared::cta.b64 p, [%0], %1;\n"
      "@p bra DONE;\n"
      "add.u32 n, n, 1;\n"
      "setp.lt.u32 p, n, %2;\n"
      "@p bra LOOP;\n"
      "trap;\n"
      "DONE:\n}" ::"r"(self(bar)), "r"(parity), "n"(SPIN_LIMIT) : "memory");
}
__device__ __forceinline__ uint32_t mbar_try(uint32_t bar, uint32_t parity) {
  uint32_t ok;
  asm volatile("{\n.reg .pred p;\nmbarrier.test_wait.parity.shared::cta.b64 p, [%1], %2;\nselp.u32 %0, 1, 0, p;\n}"
               : "=r"(ok) : "r"(self(bar)), "r"(parity) : "memory");
  return ok;
}
__device__ __forceinline__ bool elect_one() {
  uint32_t ok;
  asm volatile("{\n.reg .pred p;\nelect.sync _|p, 0xffffffff;\nselp.u32 %0, 1, 0, p;\n}" : "=r"(ok));
  return ok != 0;
}
__device__ __forceinline__ void bulk_load(uint32_t dst, const void* src, uint32_t bytes, uint32_t bar) {
  asm volatile("cp.async.bulk.shared::cluster.global.mbarrier::complete_tx::bytes [%0], [%1], %2, [%3];"
               ::"r"(self(dst)), "l"(src), "r"(bytes), "r"(self(bar)) : "memory");
}
__device__ __forceinline__ unsigned flag_wait(const unsigned* p, unsigned want) {
  unsigned v, n = 0;
  while (true) {
    asm volatile("ld.acquire.gpu.global.u32 %0, [%1];" : "=r"(v) : "l"(p) : "memory");
    if ((int)(v - want) >= 0) break;
    if (++n > SPIN_LIMIT) __trap();
  }
  return v;
}
__device__ __forceinline__ void tma2d(uint32_t dst, const CUtensorMap* m, int c0, int c1, uint32_t bar) {
  asm volatile("cp.async.bulk.tensor.2d.shared::cluster.global.mbarrier::complete_tx::bytes [%0], [%1, {%3, %4}], [%2];"
               ::"r"(self(dst)), "l"(m), "r"(self(bar)), "r"(c0), "r"(c1) : "memory");
}
__device__ __forceinline__ void tma3d(uint32_t dst, const CUtensorMap* m, int c0, int c1, int c2, uint32_t bar) {
  asm volatile("cp.async.bulk.tensor.3d.shared::cluster.global.mbarrier::complete_tx::bytes [%0], [%1, {%3, %4, %5}], [%2];"
               ::"r"(self(dst)), "l"(m), "r"(self(bar)), "r"(c0), "r"(c1), "r"(c2) : "memory");
}
__device__ __forceinline__ void prefetch_map(const CUtensorMap* m) { asm volatile("prefetch.tensormap [%0];" ::"l"(m) : "memory"); }
__device__ __forceinline__ void wg_fence() { asm volatile("wgmma.fence.sync.aligned;" ::: "memory"); }
__device__ __forceinline__ void wg_commit() { asm volatile("wgmma.commit_group.sync.aligned;" ::: "memory"); }
template <int N> __device__ __forceinline__ void wg_wait() { asm volatile("wgmma.wait_group.sync.aligned %0;" ::"n"(N) : "memory"); }
template <int N> __device__ __forceinline__ void reg_fence(float (&d)[N]) {
#pragma unroll
  for (int i = 0; i < N; i++) asm volatile("" : "+f"(d[i])::"memory");
}
template <int N> __device__ __forceinline__ void reg_fence(uint32_t (&d)[N]) {
#pragma unroll
  for (int i = 0; i < N; i++) asm volatile("" : "+r"(d[i])::"memory");
}
__device__ __forceinline__ void fence_async_smem() { asm volatile("fence.proxy.async.shared::cta;" ::: "memory"); }
__device__ __forceinline__ void fence_async_global() { asm volatile("fence.proxy.async.global;" ::: "memory"); }
__device__ __forceinline__ uint32_t pack_bf16(float lo, float hi) {
  uint32_t r;
  asm("cvt.rn.bf16x2.f32 %0, %1, %2;" : "=r"(r) : "f"(hi), "f"(lo));
  return r;
}
__device__ __forceinline__ void sts32(uint32_t a, uint32_t v) { asm volatile("st.shared.u32 [%0], %1;" ::"r"(self(a)), "r"(v) : "memory"); }
__device__ __forceinline__ void sts128(uint32_t a, uint32_t r0, uint32_t r1, uint32_t r2, uint32_t r3) {
  asm volatile("st.shared.v4.u32 [%0], {%1, %2, %3, %4};" ::"r"(self(a)), "r"(r0), "r"(r1), "r"(r2), "r"(r3) : "memory");
}
__device__ __forceinline__ uint32_t add_bf16x2(uint32_t a, uint32_t b) {
  uint32_t r;
  asm("add.rn.bf16x2 %0, %1, %2;" : "=r"(r) : "r"(a), "r"(b));
  return r;
}
__device__ __forceinline__ void stsm4(uint32_t a, uint32_t r0, uint32_t r1, uint32_t r2, uint32_t r3) {
  asm volatile("stmatrix.sync.aligned.m8n8.x4.shared.b16 [%0], {%1, %2, %3, %4};" ::"r"(self(a)), "r"(r0), "r"(r1), "r"(r2), "r"(r3) : "memory");
}
__device__ __forceinline__ float lds_f32(uint32_t a) {
  float v;
  asm volatile("ld.shared.f32 %0, [%1];" : "=f"(v) : "r"(self(a)) : "memory");
  return v;
}
__device__ __forceinline__ uint4 lds128(uint32_t a) {
  uint4 v;
  asm volatile("ld.shared.v4.u32 {%0, %1, %2, %3}, [%4];" : "=r"(v.x), "=r"(v.y), "=r"(v.z), "=r"(v.w) : "r"(self(a)) : "memory");
  return v;
}
__device__ __forceinline__ float ex2(float x) {
  float y;
  asm("ex2.approx.ftz.f32 %0, %1;" : "=f"(y) : "f"(x));
  return y;
}
__device__ __forceinline__ float tanh_fast(float x) {
  float y;
  asm("tanh.approx.f32 %0, %1;" : "=f"(y) : "f"(x));
  return y;
}
__host__ __device__ constexpr uint32_t desc_lo(uint32_t addr, uint32_t lbo) { return ((addr & 0x3FFFFu) >> 4) | ((lbo >> 4) << 16); }
__device__ __forceinline__ void sched_fence() {
  asm volatile("pmevent 0;" ::: "memory");
}

__device__ __forceinline__ void mma_qkv(float (&d)[92], uint32_t alo, uint32_t blo, uint32_t bhi, int scale_d) {
  asm volatile("{\n.reg .pred p;\n.reg .b64 da, db;\nsetp.ne.b32 p, %95, 0;\nmov.b64 da, {%92, %96};\nmov.b64 db, {%93, %94};\n"
    "wgmma.mma_async.sync.aligned.m64n184k16.f32.bf16.bf16 {"
    "%0, %1, %2, %3, %4, %5, %6, %7, %8, %9, %10, %11, %12, %13, %14, %15, "
    "%16, %17, %18, %19, %20, %21, %22, %23, %24, %25, %26, %27, %28, %29, %30, %31, "
    "%32, %33, %34, %35, %36, %37, %38, %39, %40, %41, %42, %43, %44, %45, %46, %47, "
    "%48, %49, %50, %51, %52, %53, %54, %55, %56, %57, %58, %59, %60, %61, %62, %63, "
    "%64, %65, %66, %67, %68, %69, %70, %71, %72, %73, %74, %75, %76, %77, %78, %79, "
    "%80, %81, %82, %83, %84, %85, %86, %87, %88, %89, %90, %91"
    "}, da, db, p, 1, 1, 0, 1;\n}\n"
    : "+f"(d[0]), "+f"(d[1]), "+f"(d[2]), "+f"(d[3]), "+f"(d[4]), "+f"(d[5]), "+f"(d[6]), "+f"(d[7]),
      "+f"(d[8]), "+f"(d[9]), "+f"(d[10]), "+f"(d[11]), "+f"(d[12]), "+f"(d[13]), "+f"(d[14]), "+f"(d[15]),
      "+f"(d[16]), "+f"(d[17]), "+f"(d[18]), "+f"(d[19]), "+f"(d[20]), "+f"(d[21]), "+f"(d[22]), "+f"(d[23]),
      "+f"(d[24]), "+f"(d[25]), "+f"(d[26]), "+f"(d[27]), "+f"(d[28]), "+f"(d[29]), "+f"(d[30]), "+f"(d[31]),
      "+f"(d[32]), "+f"(d[33]), "+f"(d[34]), "+f"(d[35]), "+f"(d[36]), "+f"(d[37]), "+f"(d[38]), "+f"(d[39]),
      "+f"(d[40]), "+f"(d[41]), "+f"(d[42]), "+f"(d[43]), "+f"(d[44]), "+f"(d[45]), "+f"(d[46]), "+f"(d[47]),
      "+f"(d[48]), "+f"(d[49]), "+f"(d[50]), "+f"(d[51]), "+f"(d[52]), "+f"(d[53]), "+f"(d[54]), "+f"(d[55]),
      "+f"(d[56]), "+f"(d[57]), "+f"(d[58]), "+f"(d[59]), "+f"(d[60]), "+f"(d[61]), "+f"(d[62]), "+f"(d[63]),
      "+f"(d[64]), "+f"(d[65]), "+f"(d[66]), "+f"(d[67]), "+f"(d[68]), "+f"(d[69]), "+f"(d[70]), "+f"(d[71]),
      "+f"(d[72]), "+f"(d[73]), "+f"(d[74]), "+f"(d[75]), "+f"(d[76]), "+f"(d[77]), "+f"(d[78]), "+f"(d[79]),
      "+f"(d[80]), "+f"(d[81]), "+f"(d[82]), "+f"(d[83]), "+f"(d[84]), "+f"(d[85]), "+f"(d[86]), "+f"(d[87]),
      "+f"(d[88]), "+f"(d[89]), "+f"(d[90]), "+f"(d[91])
    : "r"(alo), "r"(blo), "r"(bhi), "r"(scale_d), "r"(DESC_HI));
}
__device__ __forceinline__ void mma_n128(float (&d)[64], uint32_t alo, uint32_t blo, uint32_t bhi, int scale_d) {
  asm volatile("{\n.reg .pred p;\n.reg .b64 da, db;\nsetp.ne.b32 p, %67, 0;\nmov.b64 da, {%64, %68};\nmov.b64 db, {%65, %66};\n"
    "wgmma.mma_async.sync.aligned.m64n128k16.f32.bf16.bf16 {"
    "%0, %1, %2, %3, %4, %5, %6, %7, %8, %9, %10, %11, %12, %13, %14, %15, "
    "%16, %17, %18, %19, %20, %21, %22, %23, %24, %25, %26, %27, %28, %29, %30, %31, "
    "%32, %33, %34, %35, %36, %37, %38, %39, %40, %41, %42, %43, %44, %45, %46, %47, "
    "%48, %49, %50, %51, %52, %53, %54, %55, %56, %57, %58, %59, %60, %61, %62, %63"
    "}, da, db, p, 1, 1, 0, 1;\n}\n"
    : "+f"(d[0]), "+f"(d[1]), "+f"(d[2]), "+f"(d[3]), "+f"(d[4]), "+f"(d[5]), "+f"(d[6]), "+f"(d[7]),
      "+f"(d[8]), "+f"(d[9]), "+f"(d[10]), "+f"(d[11]), "+f"(d[12]), "+f"(d[13]), "+f"(d[14]), "+f"(d[15]),
      "+f"(d[16]), "+f"(d[17]), "+f"(d[18]), "+f"(d[19]), "+f"(d[20]), "+f"(d[21]), "+f"(d[22]), "+f"(d[23]),
      "+f"(d[24]), "+f"(d[25]), "+f"(d[26]), "+f"(d[27]), "+f"(d[28]), "+f"(d[29]), "+f"(d[30]), "+f"(d[31]),
      "+f"(d[32]), "+f"(d[33]), "+f"(d[34]), "+f"(d[35]), "+f"(d[36]), "+f"(d[37]), "+f"(d[38]), "+f"(d[39]),
      "+f"(d[40]), "+f"(d[41]), "+f"(d[42]), "+f"(d[43]), "+f"(d[44]), "+f"(d[45]), "+f"(d[46]), "+f"(d[47]),
      "+f"(d[48]), "+f"(d[49]), "+f"(d[50]), "+f"(d[51]), "+f"(d[52]), "+f"(d[53]), "+f"(d[54]), "+f"(d[55]),
      "+f"(d[56]), "+f"(d[57]), "+f"(d[58]), "+f"(d[59]), "+f"(d[60]), "+f"(d[61]), "+f"(d[62]), "+f"(d[63])
    : "r"(alo), "r"(blo), "r"(bhi), "r"(scale_d), "r"(DESC_HI));
}
__device__ __forceinline__ void mma_rs64(float (&d)[32], uint32_t a0, uint32_t a1, uint32_t a2, uint32_t a3, uint32_t blo, uint32_t bhi, int scale_d) {
  asm volatile("{\n.reg .pred p;\n.reg .b64 db;\nsetp.ne.b32 p, %38, 0;\nmov.b64 db, {%36, %37};\n"
    "wgmma.mma_async.sync.aligned.m64n64k16.f32.bf16.bf16 {"
    "%0, %1, %2, %3, %4, %5, %6, %7, %8, %9, %10, %11, %12, %13, %14, %15, "
    "%16, %17, %18, %19, %20, %21, %22, %23, %24, %25, %26, %27, %28, %29, %30, %31"
    "}, {%32, %33, %34, %35}, db, p, 1, 1, 1;\n}\n"
    : "+f"(d[0]), "+f"(d[1]), "+f"(d[2]), "+f"(d[3]), "+f"(d[4]), "+f"(d[5]), "+f"(d[6]), "+f"(d[7]),
      "+f"(d[8]), "+f"(d[9]), "+f"(d[10]), "+f"(d[11]), "+f"(d[12]), "+f"(d[13]), "+f"(d[14]), "+f"(d[15]),
      "+f"(d[16]), "+f"(d[17]), "+f"(d[18]), "+f"(d[19]), "+f"(d[20]), "+f"(d[21]), "+f"(d[22]), "+f"(d[23]),
      "+f"(d[24]), "+f"(d[25]), "+f"(d[26]), "+f"(d[27]), "+f"(d[28]), "+f"(d[29]), "+f"(d[30]), "+f"(d[31])
    : "r"(a0), "r"(a1), "r"(a2), "r"(a3), "r"(blo), "r"(bhi), "r"(scale_d));
}
__device__ __forceinline__ void mma_ss64(float (&d)[32], uint32_t alo, uint32_t blo, uint32_t bhi, int scale_d) {
  asm volatile("{\n.reg .pred p;\n.reg .b64 da, db;\nsetp.ne.b32 p, %35, 0;\nmov.b64 da, {%32, %36};\nmov.b64 db, {%33, %34};\n"
    "wgmma.mma_async.sync.aligned.m64n64k16.f32.bf16.bf16 {"
    "%0, %1, %2, %3, %4, %5, %6, %7, %8, %9, %10, %11, %12, %13, %14, %15, "
    "%16, %17, %18, %19, %20, %21, %22, %23, %24, %25, %26, %27, %28, %29, %30, %31"
    "}, da, db, p, 1, 1, 0, 1;\n}\n"
    : "+f"(d[0]), "+f"(d[1]), "+f"(d[2]), "+f"(d[3]), "+f"(d[4]), "+f"(d[5]), "+f"(d[6]), "+f"(d[7]),
      "+f"(d[8]), "+f"(d[9]), "+f"(d[10]), "+f"(d[11]), "+f"(d[12]), "+f"(d[13]), "+f"(d[14]), "+f"(d[15]),
      "+f"(d[16]), "+f"(d[17]), "+f"(d[18]), "+f"(d[19]), "+f"(d[20]), "+f"(d[21]), "+f"(d[22]), "+f"(d[23]),
      "+f"(d[24]), "+f"(d[25]), "+f"(d[26]), "+f"(d[27]), "+f"(d[28]), "+f"(d[29]), "+f"(d[30]), "+f"(d[31])
    : "r"(alo), "r"(blo), "r"(bhi), "r"(scale_d), "r"(DESC_HI));
}
__device__ __forceinline__ void mma_s(float (&d)[32], uint32_t alo, uint32_t blo, uint32_t bhi, int scale_d) {
  asm volatile("{\n.reg .pred p;\n.reg .b64 da, db;\nsetp.ne.b32 p, %35, 0;\nmov.b64 da, {%32, %36};\nmov.b64 db, {%33, %34};\n"
    "wgmma.mma_async.sync.aligned.m64n64k16.f32.bf16.bf16 {"
    "%0, %1, %2, %3, %4, %5, %6, %7, %8, %9, %10, %11, %12, %13, %14, %15, "
    "%16, %17, %18, %19, %20, %21, %22, %23, %24, %25, %26, %27, %28, %29, %30, %31"
    "}, da, db, p, 1, 1, 0, 0;\n}\n"
    : "+f"(d[0]), "+f"(d[1]), "+f"(d[2]), "+f"(d[3]), "+f"(d[4]), "+f"(d[5]), "+f"(d[6]), "+f"(d[7]),
      "+f"(d[8]), "+f"(d[9]), "+f"(d[10]), "+f"(d[11]), "+f"(d[12]), "+f"(d[13]), "+f"(d[14]), "+f"(d[15]),
      "+f"(d[16]), "+f"(d[17]), "+f"(d[18]), "+f"(d[19]), "+f"(d[20]), "+f"(d[21]), "+f"(d[22]), "+f"(d[23]),
      "+f"(d[24]), "+f"(d[25]), "+f"(d[26]), "+f"(d[27]), "+f"(d[28]), "+f"(d[29]), "+f"(d[30]), "+f"(d[31])
    : "r"(alo), "r"(blo), "r"(bhi), "r"(scale_d), "r"(DESC_HI));
}
__device__ __forceinline__ void mma_s0(float (&d)[32], uint32_t alo, uint32_t blo, uint32_t bhi) {
  asm volatile("{\n.reg .pred p;\n.reg .b64 da, db;\nsetp.ne.b32 p, %35, 0;\nmov.b64 da, {%32, %36};\nmov.b64 db, {%33, %34};\n"
    "wgmma.mma_async.sync.aligned.m64n64k16.f32.bf16.bf16 {"
    "%0, %1, %2, %3, %4, %5, %6, %7, %8, %9, %10, %11, %12, %13, %14, %15, "
    "%16, %17, %18, %19, %20, %21, %22, %23, %24, %25, %26, %27, %28, %29, %30, %31"
    "}, da, db, p, 1, 1, 0, 0;\n}\n"
    : "=f"(d[0]), "=f"(d[1]), "=f"(d[2]), "=f"(d[3]), "=f"(d[4]), "=f"(d[5]), "=f"(d[6]), "=f"(d[7]),
      "=f"(d[8]), "=f"(d[9]), "=f"(d[10]), "=f"(d[11]), "=f"(d[12]), "=f"(d[13]), "=f"(d[14]), "=f"(d[15]),
      "=f"(d[16]), "=f"(d[17]), "=f"(d[18]), "=f"(d[19]), "=f"(d[20]), "=f"(d[21]), "=f"(d[22]), "=f"(d[23]),
      "=f"(d[24]), "=f"(d[25]), "=f"(d[26]), "=f"(d[27]), "=f"(d[28]), "=f"(d[29]), "=f"(d[30]), "=f"(d[31])
    : "r"(alo), "r"(blo), "r"(bhi), "n"(0), "r"(DESC_HI));
}
__device__ __forceinline__ void mma_pv(float (&d)[16], uint32_t a0, uint32_t a1, uint32_t a2, uint32_t a3, uint32_t blo, uint32_t bhi, int scale_d) {
  asm volatile("{\n.reg .pred p;\n.reg .b64 db;\nsetp.ne.b32 p, %22, 0;\nmov.b64 db, {%20, %21};\n"
    "wgmma.mma_async.sync.aligned.m64n32k16.f32.bf16.bf16 {"
    "%0, %1, %2, %3, %4, %5, %6, %7, %8, %9, %10, %11, %12, %13, %14, %15"
    "}, {%16, %17, %18, %19}, db, p, 1, 1, 1;\n}\n"
    : "+f"(d[0]), "+f"(d[1]), "+f"(d[2]), "+f"(d[3]), "+f"(d[4]), "+f"(d[5]), "+f"(d[6]), "+f"(d[7]),
      "+f"(d[8]), "+f"(d[9]), "+f"(d[10]), "+f"(d[11]), "+f"(d[12]), "+f"(d[13]), "+f"(d[14]), "+f"(d[15])
    : "r"(a0), "r"(a1), "r"(a2), "r"(a3), "r"(blo), "r"(bhi), "r"(scale_d));
}

__device__ __forceinline__ void store_heads(uint32_t rowaddr, uint32_t lane, const uint32_t (&v)[14], uint32_t pad) {
  const uint32_t q = lane & 3;
  uint32_t o[16];
#pragma unroll
  for (int c = 0; c < 8; c++)
#pragma unroll
    for (int hf = 0; hf < 2; hf++) {
      uint32_t x = c < 7 ? v[2 * c + hf] : pad;
      if ((c & 1) && c < 7) x = q == (7u - c) / 2 ? pad : x;
      if (c >= 2) x = q >= 4u - c / 2 ? v[2 * (c - 1) + hf] : x;
      o[2 * c + hf] = x;
    }
#pragma unroll
  for (int g = 0; g < 4; g++)
    stsm4(rowaddr + (((2 * g + (lane >> 4)) ^ (lane & 7)) << 4), o[4 * g], o[4 * g + 1], o[4 * g + 2], o[4 * g + 3]);
}

constexpr float SM_C = 0.18898223650461361f * 1.4426950408889634f;

struct RowStat {
  float m0, m1;
  float al0, al1;
};

__device__ __forceinline__ void mask_block(float (&s)[32], bool diag, int row, int q) {
  const float NEG = __int_as_float(0xff800000);
  const int t0 = row - 2 * q, t1 = t0 + 8;
#pragma unroll
  for (int g = 0; g < 8; g++) {
    if (((8 * g) <= t0) != diag) s[4 * g] = NEG;
    if (((8 * g + 1) <= t0) != diag) s[4 * g + 1] = NEG;
    if (((8 * g) <= t1) != diag) s[4 * g + 2] = NEG;
    if (((8 * g + 1) <= t1) != diag) s[4 * g + 3] = NEG;
  }
}

__device__ __forceinline__ void update_max(const float (&s)[32], RowStat& r, bool first) {
  const float p0 = first ? __int_as_float(0xff800000) : r.m0, p1 = first ? __int_as_float(0xff800000) : r.m1;
  float a0 = fmaxf(s[0], s[1]), a1 = fmaxf(s[2], s[3]), b0 = fmaxf(s[4], s[5]), b1 = fmaxf(s[6], s[7]);
#pragma unroll
  for (int g = 2; g < 8; g += 2) {
    a0 = fmaxf(a0, fmaxf(s[4 * g], s[4 * g + 1]));
    a1 = fmaxf(a1, fmaxf(s[4 * g + 2], s[4 * g + 3]));
    b0 = fmaxf(b0, fmaxf(s[4 * g + 4], s[4 * g + 5]));
    b1 = fmaxf(b1, fmaxf(s[4 * g + 6], s[4 * g + 7]));
  }
  a0 = fmaxf(fmaxf(a0, b0), p0);
  a1 = fmaxf(fmaxf(a1, b1), p1);
  a0 = fmaxf(a0, __shfl_xor_sync(~0u, a0, 1));
  a1 = fmaxf(a1, __shfl_xor_sync(~0u, a1, 1));
  a0 = fmaxf(a0, __shfl_xor_sync(~0u, a0, 2));
  a1 = fmaxf(a1, __shfl_xor_sync(~0u, a1, 2));
  r.al0 = ex2(p0 - a0);
  r.al1 = ex2(p1 - a1);
  r.m0 = a0;
  r.m1 = a1;
}

__device__ __forceinline__ void exp_shifted(float (&s)[32], float m0, float m1) {
#pragma unroll
  for (int g = 0; g < 8; g++) {
    s[4 * g] = ex2(s[4 * g] - m0);
    s[4 * g + 1] = ex2(s[4 * g + 1] - m0);
    s[4 * g + 2] = ex2(s[4 * g + 2] - m1);
    s[4 * g + 3] = ex2(s[4 * g + 3] - m1);
  }
}
template <int G0, int G1> __device__ __forceinline__ void ex2_groups(float (&s)[32]) {
#pragma unroll
  for (int i = 4 * G0; i < 4 * G1; i++) s[i] = ex2(s[i]);
}
constexpr int GX = 6;

__device__ __forceinline__ void issue_s(float (&s)[32], uint32_t qlo, uint32_t klo) {
  wg_fence();
  mma_s0(s, qlo, klo, DESC_HI);
  mma_s(s, qlo + 2, klo + 2, DESC_HI, 1);
  wg_commit();
  sched_fence();
}
__device__ __forceinline__ void issue_pv(float (&o)[16], const uint32_t (&p)[16], uint32_t vlo, int acc_o) {
  wg_fence();
  mma_pv(o, p[0], p[1], p[2], p[3], vlo, DESC_HI, acc_o);
  mma_pv(o, p[4], p[5], p[6], p[7], vlo + 128, DESC_HI, 1);
  mma_pv(o, p[8], p[9], p[10], p[11], vlo + 256, DESC_HI, 1);
  mma_pv(o, p[12], p[13], p[14], p[15], vlo + 384, DESC_HI, 1);
  wg_commit();
  sched_fence();
}
__device__ __forceinline__ void issue_s_pv(float (&s)[32], uint32_t qlo, uint32_t klo, float (&o)[16], const uint32_t (&p)[16],
                                           uint32_t vlo, int acc_o) {
  wg_fence();
  mma_pv(o, p[0], p[1], p[2], p[3], vlo, DESC_HI, acc_o);
  mma_pv(o, p[4], p[5], p[6], p[7], vlo + 128, DESC_HI, 1);
  mma_pv(o, p[8], p[9], p[10], p[11], vlo + 256, DESC_HI, 1);
  mma_pv(o, p[12], p[13], p[14], p[15], vlo + 384, DESC_HI, 1);
  mma_s0(s, qlo, klo, DESC_HI);
  mma_s(s, qlo + 2, klo + 2, DESC_HI, 1);
  wg_commit();
  sched_fence();
}
__device__ __forceinline__ float rcp_fast(float x) {
  float y;
  asm("rcp.approx.ftz.f32 %0, %1;" : "=f"(y) : "f"(x));
  return y;
}
__device__ __forceinline__ void pack_p(const float (&s)[32], uint32_t (&p)[16]) {
#pragma unroll
  for (int i = 0; i < 16; i++) p[i] = pack_bf16(s[2 * i], s[2 * i + 1]);
}
struct PMask { uint32_t d[4], t[3]; };
__device__ __forceinline__ void and_xor(uint32_t& p, uint32_t m, uint32_t inv) {
  asm("lop3.b32 %0, %0, %1, %2, 0x60;" : "+r"(p) : "r"(m), "r"(inv));
}
__device__ __forceinline__ void mask_p(uint32_t (&p)[16], const PMask& mk, uint32_t inv) {
#pragma unroll
  for (int k = 0; k < 4; k++) {
    and_xor(p[4 * k], mk.d[k], inv);
    and_xor(p[4 * k + 1], k == 0 ? ~0u : mk.t[k - 1], inv);
    and_xor(p[4 * k + 2], k == 3 ? 0u : mk.t[k], inv);
    and_xor(p[4 * k + 3], mk.d[k], inv);
  }
}

template <int NG, int N>
__device__ __forceinline__ void glu_group(uint32_t* h, const float (&acc)[N], int g, float a0, float a1) {
  const float* gt = acc + 4 * g;
  const float* up = acc + 4 * (NG + g);
  const float u0 = a0 * up[0], u1 = a0 * up[1], u2 = a1 * up[2], u3 = a1 * up[3];
  h[2 * g] = pack_bf16(fmaf(u0, tanh_fast(0.5f * gt[0]), u0), fmaf(u1, tanh_fast(0.5f * gt[1]), u1));
  h[2 * g + 1] = pack_bf16(fmaf(u2, tanh_fast(0.5f * gt[2]), u2), fmaf(u3, tanh_fast(0.5f * gt[3]), u3));
  asm volatile("" : "+r"(h[2 * g]), "+r"(h[2 * g + 1])::"memory");
}

template <int IT0, int HS0, class Side>
__device__ __forceinline__ void pass64(float (&acc)[64], uint32_t xlo, bool lane0, Side side) {
#pragma unroll
  for (int hs = HS0; hs < 14; hs++) {
    const int st = hs >> 1, k = (hs & 1) * 2;
    const int slot = (IT0 + st) % NSLOT, ph = ((IT0 + st) / NSLOT) & 1;
    const uint32_t a = xlo + st * 1024 + 2 * k, b = desc_lo(OFF_RING + slot * 16384, 8192) + 128 * k;
    if (!(hs & 1)) mbar_wait(B_FULL + 8 * slot, ph);
    wg_fence();
    mma_n128(acc, a, b, DESC_HI, hs != 0);
    mma_n128(acc, a + 2, b + 128, DESC_HI, 1);
    wg_commit();
    sched_fence();
    side(hs);
    sched_fence();
    wg_wait<0>();
    if (hs & 1) mbar_arrive_if(lane0, B_EMPTY + 8 * slot);
  }
  reg_fence(acc);
}

template <int IT0, class Side>
__device__ __forceinline__ void pass32(float (&acc)[32], uint32_t xlo, bool lane0, Side side) {
#pragma unroll
  for (int hs = 0; hs < 7; hs++) {
    const int st = hs >> 1;
    const int slot = (IT0 + st) % NSLOT, ph = ((IT0 + st) / NSLOT) & 1;
    const uint32_t a = xlo + hs * 1024, b = desc_lo(OFF_RING + slot * 16384, 4096) + (hs & 1) * 512;
    if (!(hs & 1)) mbar_wait(B_FULL + 8 * slot, ph);
    wg_fence();
#pragma unroll
    for (int k = 0; k < 4; k++) mma_ss64(acc, a + 2 * k, b + 64 * k, DESC_HI64, (hs | k) != 0);
    wg_commit();
    sched_fence();
    side(hs);
    sched_fence();
    wg_wait<0>();
    if ((hs & 1) || hs == 6) mbar_arrive_if(lane0, B_EMPTY + 8 * slot);
  }
  reg_fence(acc);
}

struct Ring {
  uint32_t slot, phase;
  __device__ __forceinline__ void next() {
    if (++slot == NSLOT) { slot = 0; phase ^= 1; }
  }
};

__global__ void __cluster_dims__(2, 1, 1) __launch_bounds__(512, 1)
fused_kernel(const uint8_t* __restrict__ x, const uint8_t* __restrict__ wqkv, const __nv_bfloat16* __restrict__ gate_w,
             __nv_bfloat16* __restrict__ out, const __grid_constant__ Maps maps) {
  const int warp = __shfl_sync(~0u, (int)(threadIdx.x >> 5), 0);
  const int wg = warp >> 2;
  const int lane = threadIdx.x & 31;
  const int cl = blockIdx.x >> 1, rank = blockIdx.x & 1;
  const int pos = cl < 36 ? (cl - 4) & 7 : (cl - 36) % 7;
  const int blk = cl < 4 ? 0 : (cl < 36 ? (pos < 2 ? 1 - pos : pos) : pos + 1);
  const int k8 = cl < 4 ? cl : (cl < 36 ? ((cl - 4) >> 3) + (blk == 0 ? 4 : 0) : 4 + (cl - 36) / 7);
  const int cta = (((blk >> 1) * 4 + (k8 >> 1)) * 8 + (blk & 1) * 4 + (k8 & 1) * 2 + rank) & 127, m = cta >> 3, j = cta & 7;

  if (threadIdx.x == 0) asm volatile("prefetch.global.L2 [%0];" ::"l"(wqkv + j * 112));
  if (wg == 2) {
    const uint32_t t = threadIdx.x & 127, r0 = t >> 3, ch = t & 7;
    const uint8_t* src = x + (size_t)(m * 128 + r0) * 896 + ch * 16;
    const uint32_t dst = OFF_X + r0 * 128 + ((ch ^ (r0 & 7)) << 4);
#pragma unroll
    for (int c = 0; c < 2; c++) {
#pragma unroll
      for (int i = 0; i < 8; i++)
        asm volatile("cp.async.cg.shared.global [%0], [%1], 16;" ::"r"(self(dst + c * 16384 + i * 2048)), "l"(src + c * 128 + i * 16 * 896) : "memory");
      asm volatile("cp.async.commit_group;" ::: "memory");
    }
  } else if (warp == 12) {
    if (elect_one()) {
      TS(0);
#pragma unroll
      for (int i = 0; i < 4; i++) mbar_init(B_EFULL + 8 * i, 1);
      TS(40);
#pragma unroll
      for (int s = 0; s < 4; s++) {
        mbar_expect_tx(B_EFULL + 8 * s, QKV_STAGE_BYTES);
        tma3d(OFF_E + s * 12288, &maps.qkv, 56 * j, 32 * s, 0, B_EFULL + 8 * s);
      }
      TS(42);
    }
  } else if (warp == 13) {
    if (elect_one()) {
      if ((smem_u32(smem_raw) & 0xFFFFFFu) != SB) __trap();
#pragma unroll
      for (uint32_t b = B_FULL; b < B_EMPTY; b += 8) mbar_init(b, 1);
#pragma unroll
      for (int c = 0; c < 6; c++) mbar_expect_tx(B_LFULL + 8 * c, 8192);
    }
  } else if (warp == 15) {
    if (elect_one()) {
#pragma unroll
      for (uint32_t b = B_EMPTY; b < B_END; b += 8)
        mbar_init(b, b < B_XFULL ? 8 : 4);
    }
  } else if (warp == 14) {
    const uint8_t* gw = reinterpret_cast<const uint8_t*>(gate_w) + lane * 16;
    asm volatile("cp.async.cg.shared.global [%0], [%1], 16;" ::"r"(self(OFF_GW + lane * 16)), "l"(gw) : "memory");
    if (lane < 24) asm volatile("cp.async.cg.shared.global [%0], [%1], 16;" ::"r"(self(OFF_GW + 512 + lane * 16)), "l"(gw + 512) : "memory");
    asm volatile("cp.async.commit_group;" ::: "memory");
  }
  __syncthreads();

  if (wg == 3) {
    if (warp == 12) {
      if (elect_one()) {
#pragma unroll 1
        for (int s = 4; s < 8; s++) {
          mbar_expect_tx(B_FULL + 8 * (s - 4), QKV_STAGE_BYTES);
          tma3d(OFF_RING + (s - 4) * 16384, &maps.qkv, 56 * j, 32 * s, 0, B_FULL + 8 * (s - 4));
        }
      }
    } else if (warp == 14) {
      asm volatile("cp.async.wait_group 0;" ::: "memory");
      __syncwarp();
      unsigned short v[8];
#pragma unroll
      for (int s = 0; s < 8; s++) asm volatile("ld.shared.u16 %0, [%1];" : "=h"(v[s]) : "r"(self(OFF_GW + s * 64 + lane * 2)) : "memory");
#pragma unroll
      for (int s = 0; s < 8; s++) {
        const uint32_t buf = (s & 4) ? OFF_RING + (s & 3) * 16384 : OFF_E + (s & 3) * 12288;
        asm volatile("st.shared.u16 [%0], %1;" ::"r"(self(buf + lane * 128 + ((7 ^ (lane & 7)) << 4))), "h"(v[s]) : "memory");
      }
      __syncwarp();
      mbar_arrive_if(lane == 0, B_GW);
    }
    __syncwarp();
    asm volatile("setmaxnreg.dec.sync.aligned.u32 24;");
    if (warp == 12) {
      if (!elect_one()) return;
      const int f0 = 224 * j;
      const int fh = (j & 1) ? f0 : f0 + 192;
      const int ff = (j & 1) ? f0 + 32 : f0;
      Ring r{0, 0};
#pragma unroll 1
      for (int s = 8; s < 14; s++) {
        if (s & 4) {
          mbar_wait(B_EMPTY + 8 * r.slot, r.phase);
          mbar_expect_tx(B_FULL + 8 * r.slot, QKV_STAGE_BYTES);
          tma3d(OFF_RING + r.slot * 16384, &maps.qkv, 56 * j, 32 * s, 0, B_FULL + 8 * r.slot);
          r.next();
        } else {
          const int e = s & 3;
          mbar_wait(B_EEMPTY + 8 * e, 0);
          mbar_expect_tx(B_EFULL + 8 * e, QKV_STAGE_BYTES);
          tma3d(OFF_E + e * 12288, &maps.qkv, 56 * j, 32 * s, 0, B_EFULL + 8 * e);
        }
      }
#pragma unroll 1
      for (int ps = 0; ps < 3; ps++) {
        if (ps == 2) {
#pragma unroll 1
          for (int s = 0; s < 4; s++) {
            const uint32_t fb = B_FULL + 8 * r.slot, dst = OFF_RING + r.slot * 16384;
            mbar_wait(B_EMPTY + 8 * r.slot, r.phase);
            mbar_expect_tx(fb, s < 3 ? 16384 : 8192);
            tma2d(dst, &maps.g32, fh, 128 * s, fb);
            tma2d(dst + 4096, &maps.u32, fh, 128 * s, fb);
            if (s < 3) {
              tma2d(dst + 8192, &maps.g32, fh, 128 * s + 64, fb);
              tma2d(dst + 12288, &maps.u32, fh, 128 * s + 64, fb);
            }
            r.next();
          }
        }
#pragma unroll 1
        for (int s = 0; s < 7; s++) {
          const uint32_t fb = B_FULL + 8 * r.slot, dst = OFF_RING + r.slot * 16384;
          mbar_wait(B_EMPTY + 8 * r.slot, r.phase);
          mbar_expect_tx(fb, 16384);
          tma2d(dst, &maps.g64, ff + 64 * ps, 64 * s, fb);
          tma2d(dst + 8192, &maps.u64, ff + 64 * ps, 64 * s, fb);
          r.next();
        }
      }
      uint32_t gb = 0;
#pragma unroll 1
      for (int c = 0; c < 7; c++) {
        if (c >= 3) {
          mbar_wait(B_GEMPTY + 8 * gb, c >= 6);
        } else if (c > 0) {
#pragma unroll 1
          for (int i = 0; i < 2; i++) {
            mbar_wait(B_EMPTY + 8 * r.slot, r.phase);
            r.next();
          }
          if (c == 2) {
            mbar_arrive(B_GO);
            mbar_wait(B_ZOK, 0);
            asm volatile("mbarrier.arrive.shared::cluster.b64 _, [%0];" ::"r"(in_cta(B_GO + 8, rank ^ 1)) : "memory");
          }
        }
        const uint32_t fb = B_GFULL + 8 * gb, dst = g2_buf(gb);
        mbar_expect_tx(fb, G2_BYTES);
        const int col = g2_col(c, rank);
        tma2d(dst, &maps.down64, col, ff, fb);
        tma2d(dst + 8192, &maps.down64, col, ff + 64, fb);
        tma2d(dst + 16384, &maps.down, col, fh, fb);
        tma2d(dst + 20480, &maps.down64, col, ff + 128, fb);
        tma2d(dst + 28672, &maps.wo, col, 56 * j, fb);
        gb = gb == 2 ? 0 : gb + 1;
      }
    } else if (warp == 13) {
      const uint32_t b = cta;
      mbar_wait(B_EPOCH, 0);
      const unsigned epoch = __float_as_uint(lds_f32(OFF_EPOCH));
      const int back = lane < 2 ? lane + 1 : 0;
      const unsigned* flag = &g_ex[m >= back ? b - 8 * back : b].flag;
      const int nB = min(5, 2 * m + 2), nsteps = nB + min(5, 2 * m + 1);
      auto key_block = [&](int n) { return n < nB ? 2 * m + 1 - (nB == 5 && n >= 3 ? 7 - n : n) : 2 * m + nB - n; };
      mbar_wait(B_K1RDY, 0);
      const int settle = epoch == 1 ? 1 : nsteps;
      int seen = 0;
#pragma unroll 1
      for (int n = 1; n <= nsteps; n++) {
        if (n == settle) {
          if (lane < 3) flag_wait(flag, epoch * 8 + 5);
          __syncwarp();
          fence_async_global();
          mbar_arrive_if(lane == 0, B_SETTLED);
        }
        if (n == nsteps) break;
        const int kv = key_block(n), kk = key_block(n + 1);
        const uint32_t fb = B_KVFULL + 8 * (n & 1);
        if (n < settle) {
          const int need = lane == 0 ? (m >= 2 || n == 1 ? min(n, 4) : min(n + 1, 4)) : (m < 2 ? 0 : (n < 4 ? n - 1 : (n < 7 ? 2 : 4)));
#pragma unroll 1
          for (uint32_t it = 0; __any_sync(~0u, lane < 2 && need && seen < need); it++) {
            unsigned v;
            asm volatile("ld.relaxed.gpu.global.u32 %0, [%1];" : "=r"(v) : "l"(flag) : "memory");
            seen = v - epoch * 8;
            if (it > SPIN_LIMIT) __trap();
          }
          if (n < 4) mbar_wait(B_PUB + 8 * (m > 0 ? n - 1 : 2), 0);
          __syncwarp();
          if (n < 3) TS(22 + n);
        }
        mbar_wait(B_KVEMPTY + 8 * ((n - 1) & 1), ((n - 1) >> 1) & 1);
        if (elect_one()) {
          mbar_expect_tx(fb, (n == 1 || n + 1 == nsteps) ? 8192 : 16384);
          if (n + 1 < nsteps) bulk_load(OFF_KV + ((n + 1) & 1) * 16384, kv_block(kk, j), 8192, fb);
          if (n > 1) bulk_load(OFF_KV + (n & 1) * 16384 + 8192, kv_block(kv, j) + 8192, 8192, fb);
        }
      }
      if (!elect_one()) return;
      {
        const uint32_t peer = in_cta(SB, rank ^ 1) - SB;
        mbar_wait(B_ZOK, 0);
        fence_async_global();
        mbar_wait(B_GO + 8, 0);
#pragma unroll 1
        for (int p = 0; p < 7; p++) {
          const uint32_t tile = g2_tile(p, 0);
          const int col = g2_col(p, rank);
          mbar_wait(B_OUT + 16 * p + 8 * 0, 0);
          fence_async_smem();
          if ((p & 1) || p == 6) {
            asm volatile("cp.reduce.async.bulk.tensor.2d.global.shared::cta.add.tile.bulk_group [%0, {%2, %3}], [%1];"
                         ::"l"(&maps.out), "r"(self(tile)), "r"(col), "r"(m * 128 + 0 * 64) : "memory");
          } else {
            asm volatile("cp.async.bulk.shared::cluster.shared::cta.mbarrier::complete_tx::bytes [%0], [%1], 8192, [%2];"
                         ::"r"(peer + out_tile(p + 0)), "r"(self(tile)), "r"(peer + B_LFULL + 8 * (p + 0)) : "memory");
          }
        }
        asm volatile("cp.async.bulk.commit_group;" ::: "memory");
        asm volatile("cp.async.bulk.wait_group.read 0;" ::: "memory");
        mbar_wait(B_RCVD, 0);
        TS(21 + 0);
      }
    } else {
      if (warp == 14) {
        if (elect_one()) {
          prefetch_map(&maps.g64);
          prefetch_map(&maps.u64);
          prefetch_map(&maps.g32);
          prefetch_map(&maps.u32);
          prefetch_map(&maps.down);
          prefetch_map(&maps.down64);
          prefetch_map(&maps.wo);
          prefetch_map(&maps.out);
        }
        __syncwarp();
#pragma unroll 1
        for (int s = 8; s < 14; s++) {
          unsigned short v;
          asm volatile("ld.shared.u16 %0, [%1];" : "=h"(v) : "r"(self(OFF_GW + s * 64 + lane * 2)) : "memory");
          mbar_wait((s & 4) ? B_EMPTY + 8 * (s & 3) : B_EEMPTY + 8 * (s & 3), 0);
          const uint32_t buf = (s & 4) ? OFF_RING + (s & 3) * 16384 : OFF_E + (s & 3) * 12288;
          asm volatile("st.shared.u16 [%0], %1;" ::"r"(self(buf + lane * 128 + ((7 ^ (lane & 7)) << 4))), "h"(v) : "memory");
          fence_async_smem();
          __syncwarp();
          mbar_arrive_if(lane == 0, B_GW + 8 * (s - 7));
        }
        mbar_wait(B_PUB + 16, 0);
        uint4* z = reinterpret_cast<uint4*>(out + (size_t)(m * 128 + j * 16) * 448);
#pragma unroll 4
        for (int i = 0; i < 28; i++) z[lane + i * 32] = make_uint4(0, 0, 0, 0);
        __syncwarp();
        mbar_arrive_if(lane < 4, B_ZRDY);
        return;
      }
      if (!elect_one()) return;
      mbar_wait(B_EFULL, 0);
      const unsigned epoch = *(volatile unsigned*)&g_ex[cta].epoch + 1;
      sts32(OFF_EPOCH, epoch);
      mbar_arrive(B_EPOCH);
      *(volatile unsigned*)&g_ex[cta].epoch = epoch;
#pragma unroll 1
      for (int i = 0; i < 4; i++) {
        mbar_wait(i == 0 ? B_K1RDY : B_VRDY, 0);
        fence_async_smem();
        uint8_t* dst = g_ex[cta].kv[1 - (i >> 1)] + (i & 1) * 8192;
        asm volatile("cp.async.bulk.global.shared::cta.bulk_group [%0], [%1], 8192;" ::"l"(dst), "r"(self(OFF_KV + i * 8192)) : "memory");
        asm volatile("cp.async.bulk.commit_group;" ::: "memory");
        asm volatile("cp.async.bulk.wait_group 0;" ::: "memory");
        asm volatile("st.relaxed.gpu.global.u32 [%0], %1;" ::"l"(&g_ex[cta].flag), "r"(epoch * 8 + 1 + i) : "memory");
        if (i != 1) mbar_arrive(B_PUB + 8 * (i == 0 ? 0 : i - 1));
        if (i == 0) TS(25);
      }
      asm volatile("st.release.gpu.global.u32 [%0], %1;" ::"l"(&g_ex[cta].flag), "r"(epoch * 8 + 5) : "memory");
      TS(26);
      mbar_wait(B_ZRDY, 0);
      asm volatile("red.release.gpu.global.add.u32 [%0], 1;" ::"l"(&g_zflag[m * 8]) : "memory");
      flag_wait(&g_zflag[m * 8], epoch * 8);
      mbar_arrive(B_ZOK);
      {
        const uint32_t peer = in_cta(SB, rank ^ 1) - SB;
        mbar_wait(B_ZOK, 0);
        fence_async_global();
        mbar_wait(B_GO + 8, 0);
#pragma unroll 1
        for (int p = 0; p < 7; p++) {
          const uint32_t tile = g2_tile(p, 1);
          const int col = g2_col(p, rank);
          mbar_wait(B_OUT + 16 * p + 8 * 1, 0);
          fence_async_smem();
          if ((p & 1) || p == 6) {
            asm volatile("cp.reduce.async.bulk.tensor.2d.global.shared::cta.add.tile.bulk_group [%0, {%2, %3}], [%1];"
                         ::"l"(&maps.out), "r"(self(tile)), "r"(col), "r"(m * 128 + 1 * 64) : "memory");
          } else {
            asm volatile("cp.async.bulk.shared::cluster.shared::cta.mbarrier::complete_tx::bytes [%0], [%1], 8192, [%2];"
                         ::"r"(peer + out_tile(p + 1)), "r"(self(tile)), "r"(peer + B_LFULL + 8 * (p + 1)) : "memory");
          }
        }
        asm volatile("cp.async.bulk.commit_group;" ::: "memory");
        asm volatile("cp.async.bulk.wait_group.read 0;" ::: "memory");
        mbar_wait(B_RCVD, 0);
        TS(21 + 1);
      }
    }
  } else if (wg == 2) {
    const int t = threadIdx.x & 127;
    const bool lane0 = lane == 0;
    {
      const uint32_t r0 = t >> 3, ch = t & 7;
      const uint8_t* src = x + (size_t)(m * 128 + r0) * 896 + ch * 16;
      const uint32_t dst = OFF_X + r0 * 128 + ((ch ^ (r0 & 7)) << 4);
#pragma unroll 1
      for (int c = 2; c < 7 + XAHEAD; c++) {
        if (c < 7) {
#pragma unroll
          for (int i = 0; i < 8; i++)
            asm volatile("cp.async.cg.shared.global [%0], [%1], 16;" ::"r"(self(dst + c * 16384 + i * 2048)), "l"(src + c * 128 + i * 16 * 896) : "memory");
        }
        asm volatile("cp.async.commit_group;" ::: "memory");
        if (c >= XAHEAD) {
          asm volatile("cp.async.wait_group %0;" ::"n"(XAHEAD) : "memory");
          fence_async_smem();
          __syncwarp();
          mbar_arrive_if(lane0, B_XFULL + 8 * (c - XAHEAD));
          TS(33 + c - XAHEAD);
        }
      }
    }
    asm volatile("setmaxnreg.inc.sync.aligned.u32 152;");
    const int wi = warp & 3, q = lane & 3;
    const int row = wi * 16 + (lane >> 2);
    constexpr uint32_t QLO = desc_lo(OFF_QO, 16), KVLO = desc_lo(OFF_KV, 16);
    float sa[32], sb[32], o0[16], o1[16];
    uint32_t p[16];
    bool odd = false;
    float g0 = 0.f, g1 = 0.f;
    auto load_gate = [&](int w) {
      mbar_wait(B_GRDY, 0);
      g0 = lds_f32(OFF_G + (w * 64 + row) * 4);
      g1 = lds_f32(OFF_G + (w * 64 + row + 8) * 4);
    };
    auto finalize = [&](int w, bool check) -> bool {
      const float l00 = __shfl_sync(~0u, odd ? o0[5] : o0[4], lane | 3), l01 = __shfl_sync(~0u, odd ? o0[7] : o0[6], lane | 3);
      const float l10 = __shfl_sync(~0u, odd ? o1[13] : o1[12], lane & ~3), l11 = __shfl_sync(~0u, odd ? o1[15] : o1[14], lane & ~3);
      if (check) {
        uint32_t d[4];
#pragma unroll
        for (int i = 0; i < 4; i++) {
          const float* o = (i < 2 ? o0 : o1) + 4 + 8 * (i & 1);
          const uint32_t e = __float_as_uint(o[0]) | __float_as_uint(o[2]), f = __float_as_uint(o[1]) | __float_as_uint(o[3]);
          d[i] = odd ? e : f;
        }
        const uint32_t da = (q & 1) ? d[0] : d[1], db = (q & 1) ? d[2] : d[3];
        const uint32_t dd = (q & 2) ? da : db;
        const float lo = fminf(fminf(l00, l01), fminf(l10, l11)), hi = l00 + l01 + l10 + l11;
        if (!__all_sync(~0u, (dd << 1) == 0 && lo >= 0x1p-100f && hi <= 0x1p100f)) return false;
      }
      const float i00 = g0 * rcp_fast(l00), i01 = g1 * rcp_fast(l01);
      const float i10 = g0 * rcp_fast(l10), i11 = g1 * rcp_fast(l11);
      uint32_t v[16];
#pragma unroll
      for (int g = 0; g < 4; g++) {
        v[2 * g] = pack_bf16(o0[4 * g] * i00, o0[4 * g + 1] * i00);
        v[2 * g + 1] = pack_bf16(o0[4 * g + 2] * i01, o0[4 * g + 3] * i01);
        v[8 + 2 * g] = pack_bf16(o1[4 * g] * i10, o1[4 * g + 1] * i10);
        v[8 + 2 * g + 1] = pack_bf16(o1[4 * g + 2] * i11, o1[4 * g + 3] * i11);
      }
#pragma unroll
      for (int g = 0; g < 4; g++) sts128(OFF_QO + w * 8192 + wi * 2048 + g * 512 + lane * 16, v[4 * g], v[4 * g + 1], v[4 * g + 2], v[4 * g + 3]);
      __syncwarp();
      mbar_arrive_if(lane0, B_ORDY + 8 * w);
      TS(31 + w);
      return true;
    };
    const uint32_t tri = ((2 * q <= (lane >> 2)) ? 0xffffu : 0u) | ((2 * q + 1 <= (lane >> 2)) ? 0xffff0000u : 0u);
    PMask mk;
#pragma unroll
    for (int k = 0; k < 4; k++) {
      mk.d[k] = k == wi ? tri : (k < wi ? ~0u : 0u);
      asm volatile("" : "+r"(mk.d[k]));
      if (k < 3) {
        mk.t[k] = k < wi ? ~0u : 0u;
        asm volatile("" : "+r"(mk.t[k]));
      }
    }
#pragma unroll
    for (int i = 0; i < 16; i++) p[i] = 0u;
    mbar_wait(B_QKRDY + 8, 0);
    fence_async_smem();
    odd = __float_as_uint(lds_f32(OFF_EPOCH)) & 1;
    TS(30);
    issue_s(sa, QLO + 512, KVLO);
    wg_wait<0>();
    reg_fence(sa);
    uint32_t ctl = m >= 2 ? 012000142001u : (m == 1 ? 010014001u : 01141u);
    asm volatile("" : "+r"(ctl));
    uint32_t qd = QLO + 512;
    uint32_t kd = KVLO, kp = KVLO - 512;
    int acc_prev = 0;
    uint32_t redo = 0;
    uint32_t gbar = B_VRDY, gpar = 0, ebar = B_KVEMPTY;
    int n = 0;
#pragma unroll 1
    do {
      TA(0);
      issue_s_pv(sb, qd + 4, kd + 4, o1, p, kp + 512 + 4, acc_prev);
      TA(1);
      ex2_groups<0, GX>(sa);
      reg_fence(sa);
      const uint32_t landed = mbar_try(gbar, gpar);
      uint32_t qn = (ctl & 4) ? QLO : qd;
      uint32_t kn = (ctl >> 3) != 1 ? kd ^ 1024 : kd + 512;
      uint32_t inv = (ctl & 2) ? ~0u : 0u;
      acc_prev = !(ctl & 1);
      asm volatile("" : "+r"(qn), "+r"(kn), "+r"(inv), "+r"(acc_prev));
      sched_fence();
      TA(2);
      wg_wait<0>();
      TA(3);
      reg_fence(o1);
      reg_fence(p);
      reg_fence(sb);
      mbar_arrive_if(lane0, ebar);
      ex2_groups<GX, 8>(sa);
      pack_p(sa, p);
      if (ctl & 3) {
        mask_p(p, mk, inv);
        if (ctl & 1) {
          if (qd != QLO) {
            mbar_wait(B_VRDY, 0);
            fence_async_smem();
          } else if (!finalize(1, true)) {
            redo = 2;
          }
        }
      }
      TA(4);
      if (!landed) mbar_wait(gbar, gpar);
      TA(5);
      issue_s_pv(sa, qn, kn, o0, p, kd + 512, acc_prev);
      TA(6);
      ex2_groups<0, GX>(sb);
      reg_fence(sb);
      gbar = B_KVFULL + 8 * ((n + 1) & 1);
      gpar = (n >> 1) & 1;
      ebar ^= 8;
      kp = kd;
      kd ^= 1024;
      asm volatile("" : "+r"(gbar), "+r"(gpar), "+r"(ebar), "+r"(kp), "+r"(kd));
      sched_fence();
      wg_wait<0>();
      sched_fence();
      TA(7);
      reg_fence(o0);
      reg_fence(p);
      reg_fence(sa);
      ex2_groups<GX, 8>(sb);
      pack_p(sb, p);
      if (ctl & 3) {
        mask_p(p, mk, inv);
        if (ctl & 1) load_gate(qd != QLO);
      }
      qd = qn;
      ctl >>= 3;
      TS(44 + n);
      n++;
    } while (ctl != 1);
    issue_pv(o1, p, kp + 512 + 4, acc_prev);
    wg_wait<0>();
    reg_fence(o1);
    reg_fence(p);
    if (!finalize(0, true)) redo |= 1;
    uint32_t any;
    asm volatile("{\n.reg .pred p, q;\nsetp.ne.u32 p, %1, 0;\nbar.red.or.pred q, 1, 128, p;\nselp.u32 %0, 1, 0, q;\n}"
                 : "=r"(any) : "r"(redo) : "memory");
    if (any) {
      uint32_t ph = 0;
      RowStat r0{}, r1{};
      mbar_wait(B_SETTLED, 0);
#pragma unroll 1
      for (int w = 0; w < 2; w++) {
        const int cnt = min(5, 2 * m + 1 + w);
#pragma unroll 1
        for (int t = 0; t < cnt; t++) {
          asm volatile("bar.sync 1, 128;" ::: "memory");
          if (wi == 0 && elect_one()) {
            fence_async_global();
            mbar_expect_tx(B_SLOW, 16384);
            bulk_load(OFF_KV, kv_block(2 * m + w - t, j), 16384, B_SLOW);
          }
          mbar_wait(B_SLOW, ph);
          ph ^= 1;
          auto head = [&](float (&o)[16], RowStat& r, uint32_t hoff) {
            issue_s(sa, QLO + w * 512 + hoff, KVLO + hoff);
            wg_wait<0>();
            reg_fence(sa);
            if ((t & 3) == 0) mask_block(sa, t == 0, row, q);
            update_max(sa, r, t == 0);
            exp_shifted(sa, r.m0, r.m1);
            pack_p(sa, p);
#pragma unroll
            for (int g = 0; g < 4; g++) {
              o[4 * g] *= r.al0; o[4 * g + 1] *= r.al0; o[4 * g + 2] *= r.al1; o[4 * g + 3] *= r.al1;
            }
            issue_pv(o, p, KVLO + 512 + hoff, t != 0);
            wg_wait<0>();
            reg_fence(o);
            reg_fence(p);
          };
          head(o0, r0, 0);
          head(o1, r1, 4);
        }
        if ((redo >> w) & 1) {
          load_gate(w);
          finalize(w, false);
        }
      }
    }
    mbar_arrive_if(lane0, B_ATTDONE);
  } else {
    const int w = wg, wi = warp & 3, q = lane & 3;
    const bool lane0 = lane == 0;
    const int row = wi * 16 + (lane >> 2);
    const uint32_t xlo = desc_lo(OFF_X, 16) + w * 512;
    float acc[92];
    uint32_t vp[14], sh;
    const uint32_t srow = (wi * 16 + (lane & 7) + ((lane >> 3) & 1) * 8) * 128;
    {
      uint32_t prev = 0;
#pragma unroll
      for (int s = 0; s < 14; s++) {
        if (!(s & 1)) mbar_wait(B_XFULL + 4 * s, 0);
        const bool ring = s & 4;
        const uint32_t sl = s & 3;
        const uint32_t a = xlo + (s >> 1) * 1024 + (s & 1) * 4;
        const uint32_t b = ring ? desc_lo(OFF_RING, 4096) + sl * 1024 : desc_lo(OFF_E, 4096) + sl * 768;
        if (s == 0 || s >= 8) mbar_wait(B_GW + 8 * max(s - 7, 0), 0);
        mbar_wait((ring ? B_FULL : B_EFULL) + 8 * sl, s >> 3);
        if (s == 0) fence_async_smem();
        if (s == 0) TS(1 + w);
        wg_fence();
        mma_qkv(acc, a, b, DESC_HI, s);
        mma_qkv(acc, a + 2, b + 128, DESC_HI, 1);
        wg_commit();
        wg_wait<1>();
        mbar_arrive_if(lane0 && s > 0, prev);
        if (s == 6) asm volatile("setmaxnreg.inc.sync.aligned.u32 168;");
        prev = (ring ? B_EMPTY : B_EEMPTY) + 8 * sl;
      }
      mbar_wait(B_EPOCH, 0);
      sh = (__float_as_uint(lds_f32(OFF_EPOCH)) & 1) * 16;
      mbar_wait(B_EEMPTY + 8 * 3, 1);
      wg_wait<0>();
      mbar_arrive_if(lane0, prev);
      reg_fence(acc);
      TS(3 + w);
    }
    uint32_t h[72];
    float a0, a1;
    float accA[64], accB[64], accH[32], accC[64];
    {
      const uint32_t kvt = OFF_KV + (1 - w) * 16384 + srow;
      {
        uint32_t v[14];
#pragma unroll
        for (int i = 0; i < 14; i++) v[i] = pack_bf16(acc[32 + 2 * i], acc[32 + 2 * i + 1]);
        store_heads(kvt, lane, v, 0x3F80u << sh);
        if (w == 1) {
          __syncwarp();
          mbar_arrive_if(lane0, B_K1RDY);
        }
      }
      {
        uint32_t v[14];
#pragma unroll
        for (int i = 0; i < 14; i++) v[i] = pack_bf16(acc[2 * i] * SM_C, acc[2 * i + 1] * SM_C);
        store_heads(OFF_QO + w * 8192 + srow, lane, v, 0x71800000u >> sh);
      }
      __syncwarp();
      mbar_arrive_if(lane0, B_QKRDY + 8 * w);
      TS(5 + w);
#pragma unroll
      for (int i = 0; i < 14; i++) vp[i] = pack_bf16(acc[64 + 2 * i], acc[64 + 2 * i + 1]);
      reg_fence(vp);
    }
    uint32_t vpad;
    pass64<IT_P1, 0>(accA, xlo, lane0, [&](int hs) {
      if (hs == 0) {
        uint32_t big = 0;
#pragma unroll
        for (int i = 0; i < 14; i += 2) big = __vimax3_u16x2(big, vp[i] & 0x7fff7fffu, vp[i + 1] & 0x7fff7fffu);
        vpad = __any_sync(~0u, max(big >> 16, big & 0xffffu) >= 0x4980u) ? 0x3F803F80u : 0x3F80u << sh;
        asm volatile("" : "+r"(vpad));
      }
      if (hs == 1) {
        store_heads(OFF_KV + (1 - w) * 16384 + 8192 + srow, lane, vp, vpad);
        __syncwarp();
        mbar_arrive_if(lane0, B_VRDY);
        TS(27 + w);
      }
      if (hs == 2) {
        a0 = __expf(-__shfl_sync(~0u, acc[28], lane & ~3));
        a1 = __expf(-__shfl_sync(~0u, acc[30], lane & ~3));
        asm volatile("" : "+f"(a0), "+f"(a1));
      }
      if (hs == 3) {
        const float g0 = __fdividef(1.f, 1.f + a0), g1 = __fdividef(1.f, 1.f + a1);
        sts32(OFF_G + (w * 64 + row + (q & 1) * 8) * 4, __float_as_uint((q & 1) ? g1 : g0));
        a0 = 0.5f - 0.5f * g0;
        a1 = 0.5f - 0.5f * g1;
        __syncwarp();
        mbar_arrive_if(lane0, B_GRDY);
      }
    });
    TS(7 + w);
    pass64<IT_P2, 0>(accB, xlo, lane0, [&](int hs) { if (!(hs & 1)) glu_group<8>(h, accA, hs >> 1, a0, a1); if (hs == 1) glu_group<8>(h, accA, 7, a0, a1); });
    TS(9 + w);
    pass32<IT_P3>(accH, xlo, lane0, [&](int hs) {
      glu_group<8>(h + 16, accB, hs, a0, a1);
      if (hs == 0) glu_group<8>(h + 16, accB, 7, a0, a1);
    });
    TS(11 + w);
    pass64<IT_P4, 0>(accC, xlo, lane0, [&](int hs) { if (hs < 8 && !(hs & 1)) glu_group<4>(h + 32, accH, hs >> 1, a0, a1); });
    TS(13 + w);
    {
      float acc0[32], acc1[32];
      const uint32_t slot0 = wi * 2048 + ((lane & 7) + ((lane >> 3) & 1) * 8) * 128;
      auto slot = [&](int g) { return slot0 + (((2 * g + (lane >> 4)) ^ (lane & 7)) << 4); };
      auto mma_k = [&](float (&acc)[32], uint32_t b, int k) {
        mma_rs64(acc, h[4 * k], h[4 * k + 1], h[4 * k + 2], h[4 * k + 3], b + k * 128, DESC_HI, k);
      };
      {
        constexpr uint32_t b = desc_lo(g2_buf(0), 4096);
        mbar_wait(B_GFULL, 0);
        wg_fence();
#pragma unroll
        for (int k = 0; k < 6; k++) mma_k(acc0, b, k);
        wg_commit();
        sched_fence();
#pragma unroll
        for (int g = 0; g < 4; g++) glu_group<8>(h + 40, accC, g, a0, a1);
        wg_fence();
#pragma unroll
        for (int k = 6; k < 12; k++) mma_k(acc0, b, k);
        wg_commit();
        sched_fence();
#pragma unroll
        for (int g = 4; g < 8; g++) glu_group<8>(h + 40, accC, g, a0, a1);
        mbar_wait(B_ORDY + 8 * w, 0);
        TS(15 + w);
#pragma unroll
        for (int g = 0; g < 4; g++) {
          const uint4 r = lds128(OFF_QO + w * 8192 + wi * 2048 + g * 512 + lane * 16);
          h[56 + 4 * g] = r.x; h[57 + 4 * g] = r.y; h[58 + 4 * g] = r.z; h[59 + 4 * g] = r.w;
        }
#pragma unroll
        for (int i = 2; i < 14; i++) h[56 + i] = q >= (8 - i / 2) / 2 ? h[58 + i] : h[56 + i];
        h[70] = h[71] = 0u;
        wg_fence();
#pragma unroll
        for (int k = 12; k < 18; k++) mma_k(acc0, b, k);
        wg_commit();
        mbar_wait(B_GO, 0);
      }
      uint32_t gb = 1;
      auto fetch_peer = [&](uint4 (&x)[4], int p) {
        mbar_wait(B_LFULL + 8 * (2 * ((p >> 1) - 1) + w), 0);
#pragma unroll
        for (int g = 0; g < 4; g++) x[g] = lds128(g2_tile(p, w) + slot(g));
      };
      auto stage_sum = [&](const uint32_t (&v)[16], const uint4 (&x)[4], int p) {
#pragma unroll
        for (int g = 0; g < 4; g++)
          stsm4(g2_tile(p, w) + slot(g), add_bf16x2(v[4 * g], x[g].x), add_bf16x2(v[4 * g + 1], x[g].y),
                add_bf16x2(v[4 * g + 2], x[g].z), add_bf16x2(v[4 * g + 3], x[g].w));
        __syncwarp();
        mbar_arrive_if(lane0, B_OUT + 16 * p + 8 * w);
      };
      auto chunk = [&](float (&acc)[32], float (&prv)[32], int c, bool send) {
        const uint32_t b = desc_lo(0, 4096) + (g2_buf(gb) >> 4);
        mbar_wait(B_GFULL + 8 * gb, c >= 3 && c < 6);
        wg_fence();
#pragma unroll
        for (int k = 0; k < G2A; k++) mma_k(acc, b, k);
        wg_commit();
        wg_wait<1>();
        reg_fence(prv);
        mbar_arrive_if(lane0, B_GEMPTY + 8 * (gb == 0 ? 2 : gb - 1));
        uint32_t v[16];
#pragma unroll
        for (int i = 0; i < 16; i++) v[i] = pack_bf16(prv[2 * i], prv[2 * i + 1]);
        if (send) {
          if (c == 3) mbar_wait(B_ATTDONE, 0);
#pragma unroll
          for (int g = 0; g < 4; g++) sts128(g2_tile(c - 1, w) + slot(g), v[4 * g], v[4 * g + 1], v[4 * g + 2], v[4 * g + 3]);
          __syncwarp();
          mbar_arrive_if(lane0, B_OUT + 16 * (c - 1) + 8 * w);
          wg_fence();
#pragma unroll
          for (int k = G2A; k < 18; k++) mma_k(acc, b, k);
          wg_commit();
        } else {
          uint4 x[4] = {};
          reg_fence(v);
          if (c > 2) fetch_peer(x, c - 1);
          wg_fence();
#pragma unroll
          for (int k = G2A; k < G2B; k++) mma_k(acc, b, k);
          wg_commit();
          sched_fence();
          stage_sum(v, x, c - 1);
          wg_fence();
#pragma unroll
          for (int k = G2B; k < 18; k++) mma_k(acc, b, k);
          wg_commit();
        }
        TS((w == 1 ? 53 : 70) + c);
        gb = gb == 2 ? 0 : gb + 1;
      };
#pragma unroll 1
      for (int c = 1; c < 7; c += 2) {
        chunk(acc1, acc0, c, true);
        chunk(acc0, acc1, c + 1, false);
      }
      {
        uint32_t v[16];
        uint4 x[4];
        fetch_peer(x, 6);
        if (lane0) asm volatile("mbarrier.arrive.shared::cluster.b64 _, [%0];" ::"r"(in_cta(B_RCVD, rank ^ 1)) : "memory");
        sched_fence();
        wg_wait<0>();
        TS(17 + w);
        reg_fence(acc0);
#pragma unroll
        for (int i = 0; i < 16; i++) v[i] = pack_bf16(acc0[2 * i], acc0[2 * i + 1]);
        stage_sum(v, x, 6);
      }
    }
  }
}

typedef CUresult (*EncodeFn)(CUtensorMap*, CUtensorMapDataType, cuuint32_t, void*, const cuuint64_t*, const cuuint64_t*,
                             const cuuint32_t*, const cuuint32_t*, CUtensorMapInterleave, CUtensorMapSwizzle,
                             CUtensorMapL2promotion, CUtensorMapFloatOOBfill);

void encode(EncodeFn fn, CUtensorMap* m, const void* p, int rank, const cuuint64_t* dims, const cuuint64_t* strides,
            const cuuint32_t* box, CUtensorMapSwizzle sw = CU_TENSOR_MAP_SWIZZLE_128B) {
  const cuuint32_t es[3] = {1, 1, 1};
  fn(m, CU_TENSOR_MAP_DATA_TYPE_BFLOAT16, rank, const_cast<void*>(p), dims, strides, box, es, CU_TENSOR_MAP_INTERLEAVE_NONE,
     sw, CU_TENSOR_MAP_L2_PROMOTION_L2_128B, CU_TENSOR_MAP_FLOAT_OOB_FILL_NONE);
}
void encode2d(EncodeFn fn, CUtensorMap* m, const void* p, uint64_t cols, uint64_t rows, uint32_t bc, uint32_t br,
              CUtensorMapSwizzle sw = CU_TENSOR_MAP_SWIZZLE_128B) {
  const cuuint64_t dims[2] = {cols, rows}, strides[1] = {cols * 2};
  const cuuint32_t box[2] = {bc, br};
  encode(fn, m, p, 2, dims, strides, box, sw);
}

}

extern "C" void kernel_launch(void* const* d_in, const int* in_sizes, int n_in, void* d_out, int out_size) {
  (void)in_sizes; (void)n_in; (void)out_size;
  void* fp = nullptr;
  cudaDriverEntryPointQueryResult qr;
  cudaGetDriverEntryPoint("cuTensorMapEncodeTiled", &fp, cudaEnableDefault, &qr);
  EncodeFn fn = (EncodeFn)fp;
  Maps maps;
  {
    const cuuint64_t dims[3] = {448, 448, 3}, strides[2] = {1344 * 2, 448 * 2};
    const cuuint32_t box[3] = {56, 32, 3};
    encode(fn, &maps.qkv, d_in[1], 3, dims, strides, box);
  }
  encode2d(fn, &maps.g64, d_in[4], 1792, 448, 64, 64);
  encode2d(fn, &maps.g32, d_in[4], 1792, 448, 32, 64, CU_TENSOR_MAP_SWIZZLE_64B);
  encode2d(fn, &maps.u64, d_in[5], 1792, 448, 64, 64);
  encode2d(fn, &maps.u32, d_in[5], 1792, 448, 32, 64, CU_TENSOR_MAP_SWIZZLE_64B);
  encode2d(fn, &maps.down, d_in[6], 448, 1792, 64, 32);
  encode2d(fn, &maps.down64, d_in[6], 448, 1792, 64, 64);
  encode2d(fn, &maps.wo, d_in[2], 448, 448, 64, 64);
  encode2d(fn, &maps.out, d_out, 448, 2048, 64, 64);
  cudaFuncSetAttribute(fused_kernel, cudaFuncAttributeMaxDynamicSharedMemorySize, SMEM_BYTES);
  fused_kernel<<<128, 512, SMEM_BYTES>>>((const uint8_t*)d_in[0], (const uint8_t*)d_in[1], (const __nv_bfloat16*)d_in[7],
                                         (__nv_bfloat16*)d_out, maps);
}
```

```cpp
#include <cuda_runtime.h>
#include <cuda_bf16.h>
#include <cuda.h>
#include <stdint.h>

namespace {

constexpr int NSLOT = 4;
constexpr int XAHEAD = 2;
constexpr uint32_t SB = 0x400;
constexpr uint32_t OFF_X = SB;
constexpr uint32_t OFF_QO = OFF_X + 114688;
constexpr uint32_t OFF_KV = OFF_QO + 16384;
constexpr uint32_t OFF_E = OFF_QO;
constexpr uint32_t OFF_RING = OFF_KV + 32768;
constexpr uint32_t OFF_BAR = OFF_RING + NSLOT * 16384;
constexpr uint32_t OFF_G = OFF_BAR + 768;
constexpr uint32_t OFF_EPOCH = OFF_G + 512;
constexpr uint32_t OFF_GW = OFF_EPOCH + 128;
constexpr uint32_t OFF_TS = OFF_GW + 896;
constexpr uint32_t SMEM_BYTES = OFF_TS + 384 - SB;

constexpr uint32_t B_EFULL = OFF_BAR;
constexpr uint32_t B_FULL = B_EFULL + 8 * 4;
constexpr uint32_t B_KVFULL = B_FULL + 8 * NSLOT;
constexpr uint32_t B_ZOK = B_KVFULL + 8 * 2;
constexpr uint32_t B_SLOW = B_ZOK + 8;
constexpr uint32_t B_SETTLED = B_SLOW + 8;
constexpr uint32_t B_PUB = B_SETTLED + 8;
constexpr uint32_t B_GW = B_PUB + 8 * 3;
constexpr uint32_t B_GFULL = B_GW + 8 * 15;
constexpr uint32_t B_GO = B_GFULL + 8 * 3;
constexpr uint32_t B_LFULL = B_GO + 8 * 2;
constexpr uint32_t B_SHIPPED = B_LFULL + 8 * 6;
constexpr uint32_t B_EPOCH = B_SHIPPED + 8 * 2;
constexpr uint32_t B_EMPTY = B_EPOCH + 8;
constexpr uint32_t B_EEMPTY = B_EMPTY + 8 * NSLOT;
constexpr uint32_t B_GEMPTY = B_EEMPTY + 8 * 4;
constexpr uint32_t B_VRDY = B_GEMPTY + 8 * 3;
constexpr uint32_t B_GRDY = B_VRDY + 8;
constexpr uint32_t B_RCVD = B_GRDY + 8;
constexpr uint32_t B_XFULL = B_RCVD + 8;
constexpr uint32_t B_KVEMPTY = B_XFULL + 8 * 7;
constexpr uint32_t B_QKRDY = B_KVEMPTY + 8 * 2;
constexpr uint32_t B_ORDY = B_QKRDY + 8 * 2;
constexpr uint32_t B_ZRDY = B_ORDY + 8 * 2;
constexpr uint32_t B_K1RDY = B_ZRDY + 8;
constexpr uint32_t B_ATTDONE = B_K1RDY + 8;
constexpr uint32_t B_OUT = B_ATTDONE + 8;
constexpr uint32_t B_END = B_OUT + 8 * 14;
static_assert(B_KVEMPTY % 16 == 0, "toggled with ^ 8");
static_assert(B_END <= OFF_G, "barriers overflow");

constexpr uint32_t DESC_HI = 0x40000040u;
constexpr uint32_t DESC_HI64 = 0x80000020u;
constexpr uint32_t SPIN_LIMIT = 1u << 18;
constexpr uint32_t POLL_LIMIT = 1u << 23;

constexpr int IT_P1 = 6, IT_P2 = 13, IT_P3 = 20, IT_P4 = 24;
constexpr uint32_t G2_BYTES = 36864;
constexpr int G2A = 4, G2B = 9;
__host__ __device__ constexpr uint32_t g2_buf(uint32_t i) { return i < 2 ? OFF_X + i * G2_BYTES : OFF_RING; }
__host__ __device__ constexpr uint32_t out_tile(uint32_t i) { return i < 5 ? OFF_X + 73728 + i * 8192 : OFF_RING + i * 8192; }

__device__ __forceinline__ int g2_col(int p, int rank) {
  return 64 * (p == 1 ? 6 : ((p & 1) || p == 6 ? 3 - 3 * rank + (p >> 1) - 1 : 3 * rank + (p >> 1)));
}

__device__ __forceinline__ uint32_t g2_tile(int p, int w) {
  return p == 1 ? OFF_QO + w * 8192
                : ((p & 1) || p == 6 ? out_tile(2 * ((p >> 1) - 1) + w) : (p == 0 ? out_tile(6) : OFF_KV + (p - 2) * 8192) + w * 8192);
}

struct alignas(64) Maps {
  CUtensorMap qkv, g64, g32, u64, u32, down, down64, wo, out;
};

struct alignas(128) Exchange {
  uint8_t kv[2][16384];
  unsigned flag, epoch;
};
__device__ Exchange g_ex[128];
__device__ unsigned g_zflag[16 * 8];
__device__ __forceinline__ const uint8_t* kv_block(int kb, int j) { return g_ex[(kb >> 1) * 8 + j].kv[kb & 1]; }
#define TS(i)
#define TA(i)

__device__ __forceinline__ uint32_t smem_u32(const void* p) { return (uint32_t)__cvta_generic_to_shared(p); }
extern __shared__ __align__(1024) uint8_t smem_raw[];
__device__ __forceinline__ uint32_t self(uint32_t a) { return a + (smem_u32(smem_raw) - SB); }
__device__ __forceinline__ uint32_t in_cta(uint32_t a, uint32_t rank) {
  uint32_t r;
  asm("mapa.shared::cluster.u32 %0, %1, %2;" : "=r"(r) : "r"(self(a)), "r"(rank));
  return r;
}
__device__ __forceinline__ void mbar_init(uint32_t bar, uint32_t cnt) {
  asm volatile("mbarrier.init.shared::cta.b64 [%0], %1;" ::"r"(self(bar)), "r"(cnt) : "memory");
}
__device__ __forceinline__ void mbar_expect_tx(uint32_t bar, uint32_t bytes) {
  asm volatile("mbarrier.arrive.expect_tx.shared::cta.b64 _, [%0], %1;" ::"r"(self(bar)), "r"(bytes) : "memory");
}
__device__ __forceinline__ void mbar_arrive(uint32_t bar) {
  asm volatile("mbarrier.arrive.shared::cta.b64 _, [%0];" ::"r"(self(bar)) : "memory");
}
__device__ __forceinline__ void mbar_arrive_if(bool pred, uint32_t bar) {
  asm volatile("{\n.reg .pred p;\nsetp.ne.u32 p, %1, 0;\n@p mbarrier.arrive.shared::cta.b64 _, [%0];\n}" ::"r"(self(bar)), "r"((uint32_t)pred) : "memory");
}
__device__ __forceinline__ void mbar_wait(uint32_t bar, uint32_t parity) {
  asm volatile(
      "{\n.reg .pred p;\n.reg .u32 n;\n"
      "mbarrier.try_wait.parity.shared::cta.b64 p, [%0], %1;\n"
      "@p bra DONE;\n"
      "mov.u32 n, 0;\n"
      "LOOP:\n"
      "mbarrier.try_wait.parity.shared::cta.b64 p, [%0], %1, 20000;\n"
      "@p bra DONE;\n"
      "add.u32 n, n, 1;\n"
      "setp.lt.u32 p, n, %2;\n"
      "@p bra LOOP;\n"
      "trap;\n"
      "DONE:\n}" ::"r"(self(bar)), "r"(parity), "n"(SPIN_LIMIT) : "memory");
}
__device__ __forceinline__ uint32_t mbar_try(uint32_t bar, uint32_t parity) {
  uint32_t ok;
  asm volatile("{\n.reg .pred p;\nmbarrier.test_wait.parity.shared::cta.b64 p, [%1], %2;\nselp.u32 %0, 1, 0, p;\n}"
               : "=r"(ok) : "r"(self(bar)), "r"(parity) : "memory");
  return ok;
}
__device__ __forceinline__ bool elect_one() {
  uint32_t ok;
  asm volatile("{\n.reg .pred p;\nelect.sync _|p, 0xffffffff;\nselp.u32 %0, 1, 0, p;\n}" : "=r"(ok));
  return ok != 0;
}
__device__ __forceinline__ void bulk_load(uint32_t dst, const void* src, uint32_t bytes, uint32_t bar) {
  asm volatile("cp.async.bulk.shared::cluster.global.mbarrier::complete_tx::bytes [%0], [%1], %2, [%3];"
               ::"r"(self(dst)), "l"(src), "r"(bytes), "r"(self(bar)) : "memory");
}
__device__ __forceinline__ unsigned flag_wait(const unsigned* p, unsigned want) {
  unsigned v, n = 0;
  while (true) {
    asm volatile("ld.acquire.gpu.global.u32 %0, [%1];" : "=r"(v) : "l"(p) : "memory");
    if ((int)(v - want) >= 0) break;
    if (++n > POLL_LIMIT) __trap();
  }
  return v;
}
__device__ __forceinline__ void tma2d(uint32_t dst, const CUtensorMap* m, int c0, int c1, uint32_t bar) {
  asm volatile("cp.async.bulk.tensor.2d.shared::cluster.global.mbarrier::complete_tx::bytes [%0], [%1, {%3, %4}], [%2];"
               ::"r"(self(dst)), "l"(m), "r"(self(bar)), "r"(c0), "r"(c1) : "memory");
}
__device__ __forceinline__ void tma3d(uint32_t dst, const CUtensorMap* m, int c0, int c1, int c2, uint32_t bar) {
  asm volatile("cp.async.bulk.tensor.3d.shared::cluster.global.mbarrier::complete_tx::bytes [%0], [%1, {%3, %4, %5}], [%2];"
               ::"r"(self(dst)), "l"(m), "r"(self(bar)), "r"(c0), "r"(c1), "r"(c2) : "memory");
}
__device__ __forceinline__ void wg_fence() { asm volatile("wgmma.fence.sync.aligned;" ::: "memory"); }
__device__ __forceinline__ void wg_commit() { asm volatile("wgmma.commit_group.sync.aligned;" ::: "memory"); }
template <int N> __device__ __forceinline__ void wg_wait() { asm volatile("wgmma.wait_group.sync.aligned %0;" ::"n"(N) : "memory"); }
template <int N> __device__ __forceinline__ void reg_fence(float (&d)[N]) {
#pragma unroll
  for (int i = 0; i < N; i++) asm volatile("" : "+f"(d[i])::"memory");
}
template <int N> __device__ __forceinline__ void reg_fence(uint32_t (&d)[N]) {
#pragma unroll
  for (int i = 0; i < N; i++) asm volatile("" : "+r"(d[i])::"memory");
}
__device__ __forceinline__ void fence_async_smem() { asm volatile("fence.proxy.async.shared::cta;" ::: "memory"); }
__device__ __forceinline__ void fence_async_global() { asm volatile("fence.proxy.async.global;" ::: "memory"); }
__device__ __forceinline__ uint32_t pack_bf16(float lo, float hi) {
  uint32_t r;
  asm("cvt.rn.bf16x2.f32 %0, %1, %2;" : "=r"(r) : "f"(hi), "f"(lo));
  return r;
}
__device__ __forceinline__ void sts32(uint32_t a, uint32_t v) { asm volatile("st.shared.u32 [%0], %1;" ::"r"(self(a)), "r"(v) : "memory"); }
__device__ __forceinline__ void sts128(uint32_t a, uint32_t r0, uint32_t r1, uint32_t r2, uint32_t r3) {
  asm volatile("st.shared.v4.u32 [%0], {%1, %2, %3, %4};" ::"r"(self(a)), "r"(r0), "r"(r1), "r"(r2), "r"(r3) : "memory");
}
__device__ __forceinline__ uint32_t add_bf16x2(uint32_t a, uint32_t b) {
  uint32_t r;
  asm("add.rn.bf16x2 %0, %1, %2;" : "=r"(r) : "r"(a), "r"(b));
  return r;
}
__device__ __forceinline__ void stsm4(uint32_t a, uint32_t r0, uint32_t r1, uint32_t r2, uint32_t r3) {
  asm volatile("stmatrix.sync.aligned.m8n8.x4.shared.b16 [%0], {%1, %2, %3, %4};" ::"r"(self(a)), "r"(r0), "r"(r1), "r"(r2), "r"(r3) : "memory");
}
__device__ __forceinline__ float lds_f32(uint32_t a) {
  float v;
  asm volatile("ld.shared.f32 %0, [%1];" : "=f"(v) : "r"(self(a)) : "memory");
  return v;
}
__device__ __forceinline__ uint4 lds128(uint32_t a) {
  uint4 v;
  asm volatile("ld.shared.v4.u32 {%0, %1, %2, %3}, [%4];" : "=r"(v.x), "=r"(v.y), "=r"(v.z), "=r"(v.w) : "r"(self(a)) : "memory");
  return v;
}
__device__ __forceinline__ float ex2(float x) {
  float y;
  asm("ex2.approx.ftz.f32 %0, %1;" : "=f"(y) : "f"(x));
  return y;
}
__device__ __forceinline__ float tanh_fast(float x) {
  float y;
  asm("tanh.approx.f32 %0, %1;" : "=f"(y) : "f"(x));
  return y;
}
__host__ __device__ constexpr uint32_t desc_lo(uint32_t addr, uint32_t lbo) { return ((addr & 0x3FFFFu) >> 4) | ((lbo >> 4) << 16); }
__device__ __forceinline__ void sched_fence() {
  asm volatile("pmevent 0;" ::: "memory");
}

__device__ __forceinline__ void mma_qkv(float (&d)[92], uint32_t alo, uint32_t blo, uint32_t bhi, int scale_d) {
  asm volatile("{\n.reg .pred p;\n.reg .b64 da, db;\nsetp.ne.b32 p, %95, 0;\nmov.b64 da, {%92, %96};\nmov.b64 db, {%93, %94};\n"
    "wgmma.mma_async.sync.aligned.m64n184k16.f32.bf16.bf16 {"
    "%0, %1, %2, %3, %4, %5, %6, %7, %8, %9, %10, %11, %12, %13, %14, %15, "
    "%16, %17, %18, %19, %20, %21, %22, %23, %24, %25, %26, %27, %28, %29, %30, %31, "
    "%32, %33, %34, %35, %36, %37, %38, %39, %40, %41, %42, %43, %44, %45, %46, %47, "
    "%48, %49, %50, %51, %52, %53, %54, %55, %56, %57, %58, %59, %60, %61, %62, %63, "
    "%64, %65, %66, %67, %68, %69, %70, %71, %72, %73, %74, %75, %76, %77, %78, %79, "
    "%80, %81, %82, %83, %84, %85, %86, %87, %88, %89, %90, %91"
    "}, da, db, p, 1, 1, 0, 1;\n}\n"
    : "+f"(d[0]), "+f"(d[1]), "+f"(d[2]), "+f"(d[3]), "+f"(d[4]), "+f"(d[5]), "+f"(d[6]), "+f"(d[7]),
      "+f"(d[8]), "+f"(d[9]), "+f"(d[10]), "+f"(d[11]), "+f"(d[12]), "+f"(d[13]), "+f"(d[14]), "+f"(d[15]),
      "+f"(d[16]), "+f"(d[17]), "+f"(d[18]), "+f"(d[19]), "+f"(d[20]), "+f"(d[21]), "+f"(d[22]), "+f"(d[23]),
      "+f"(d[24]), "+f"(d[25]), "+f"(d[26]), "+f"(d[27]), "+f"(d[28]), "+f"(d[29]), "+f"(d[30]), "+f"(d[31]),
      "+f"(d[32]), "+f"(d[33]), "+f"(d[34]), "+f"(d[35]), "+f"(d[36]), "+f"(d[37]), "+f"(d[38]), "+f"(d[39]),
      "+f"(d[40]), "+f"(d[41]), "+f"(d[42]), "+f"(d[43]), "+f"(d[44]), "+f"(d[45]), "+f"(d[46]), "+f"(d[47]),
      "+f"(d[48]), "+f"(d[49]), "+f"(d[50]), "+f"(d[51]), "+f"(d[52]), "+f"(d[53]), "+f"(d[54]), "+f"(d[55]),
      "+f"(d[56]), "+f"(d[57]), "+f"(d[58]), "+f"(d[59]), "+f"(d[60]), "+f"(d[61]), "+f"(d[62]), "+f"(d[63]),
      "+f"(d[64]), "+f"(d[65]), "+f"(d[66]), "+f"(d[67]), "+f"(d[68]), "+f"(d[69]), "+f"(d[70]), "+f"(d[71]),
      "+f"(d[72]), "+f"(d[73]), "+f"(d[74]), "+f"(d[75]), "+f"(d[76]), "+f"(d[77]), "+f"(d[78]), "+f"(d[79]),
      "+f"(d[80]), "+f"(d[81]), "+f"(d[82]), "+f"(d[83]), "+f"(d[84]), "+f"(d[85]), "+f"(d[86]), "+f"(d[87]),
      "+f"(d[88]), "+f"(d[89]), "+f"(d[90]), "+f"(d[91])
    : "r"(alo), "r"(blo), "r"(bhi), "r"(scale_d), "r"(DESC_HI));
}
__device__ __forceinline__ void mma_n128(float (&d)[64], uint32_t alo, uint32_t blo, uint32_t bhi, int scale_d) {
  asm volatile("{\n.reg .pred p;\n.reg .b64 da, db;\nsetp.ne.b32 p, %67, 0;\nmov.b64 da, {%64, %68};\nmov.b64 db, {%65, %66};\n"
    "wgmma.mma_async.sync.aligned.m64n128k16.f32.bf16.bf16 {"
    "%0, %1, %2, %3, %4, %5, %6, %7, %8, %9, %10, %11, %12, %13, %14, %15, "
    "%16, %17, %18, %19, %20, %21, %22, %23, %24, %25, %26, %27, %28, %29, %30, %31, "
    "%32, %33, %34, %35, %36, %37, %38, %39, %40, %41, %42, %43, %44, %45, %46, %47, "
    "%48, %49, %50, %51, %52, %53, %54, %55, %56, %57, %58, %59, %60, %61, %62, %63"
    "}, da, db, p, 1, 1, 0, 1;\n}\n"
    : "+f"(d[0]), "+f"(d[1]), "+f"(d[2]), "+f"(d[3]), "+f"(d[4]), "+f"(d[5]), "+f"(d[6]), "+f"(d[7]),
      "+f"(d[8]), "+f"(d[9]), "+f"(d[10]), "+f"(d[11]), "+f"(d[12]), "+f"(d[13]), "+f"(d[14]), "+f"(d[15]),
      "+f"(d[16]), "+f"(d[17]), "+f"(d[18]), "+f"(d[19]), "+f"(d[20]), "+f"(d[21]), "+f"(d[22]), "+f"(d[23]),
      "+f"(d[24]), "+f"(d[25]), "+f"(d[26]), "+f"(d[27]), "+f"(d[28]), "+f"(d[29]), "+f"(d[30]), "+f"(d[31]),
      "+f"(d[32]), "+f"(d[33]), "+f"(d[34]), "+f"(d[35]), "+f"(d[36]), "+f"(d[37]), "+f"(d[38]), "+f"(d[39]),
      "+f"(d[40]), "+f"(d[41]), "+f"(d[42]), "+f"(d[43]), "+f"(d[44]), "+f"(d[45]), "+f"(d[46]), "+f"(d[47]),
      "+f"(d[48]), "+f"(d[49]), "+f"(d[50]), "+f"(d[51]), "+f"(d[52]), "+f"(d[53]), "+f"(d[54]), "+f"(d[55]),
      "+f"(d[56]), "+f"(d[57]), "+f"(d[58]), "+f"(d[59]), "+f"(d[60]), "+f"(d[61]), "+f"(d[62]), "+f"(d[63])
    : "r"(alo), "r"(blo), "r"(bhi), "r"(scale_d), "r"(DESC_HI));
}
__device__ __forceinline__ void mma_rs64(float (&d)[32], uint32_t a0, uint32_t a1, uint32_t a2, uint32_t a3, uint32_t blo, uint32_t bhi, int scale_d) {
  asm volatile("{\n.reg .pred p;\n.reg .b64 db;\nsetp.ne.b32 p, %38, 0;\nmov.b64 db, {%36, %37};\n"
    "wgmma.mma_async.sync.aligned.m64n64k16.f32.bf16.bf16 {"
    "%0, %1, %2, %3, %4, %5, %6, %7, %8, %9, %10, %11, %12, %13, %14, %15, "
    "%16, %17, %18, %19, %20, %21, %22, %23, %24, %25, %26, %27, %28, %29, %30, %31"
    "}, {%32, %33, %34, %35}, db, p, 1, 1, 1;\n}\n"
    : "+f"(d[0]), "+f"(d[1]), "+f"(d[2]), "+f"(d[3]), "+f"(d[4]), "+f"(d[5]), "+f"(d[6]), "+f"(d[7]),
      "+f"(d[8]), "+f"(d[9]), "+f"(d[10]), "+f"(d[11]), "+f"(d[12]), "+f"(d[13]), "+f"(d[14]), "+f"(d[15]),
      "+f"(d[16]), "+f"(d[17]), "+f"(d[18]), "+f"(d[19]), "+f"(d[20]), "+f"(d[21]), "+f"(d[22]), "+f"(d[23]),
      "+f"(d[24]), "+f"(d[25]), "+f"(d[26]), "+f"(d[27]), "+f"(d[28]), "+f"(d[29]), "+f"(d[30]), "+f"(d[31])
    : "r"(a0), "r"(a1), "r"(a2), "r"(a3), "r"(blo), "r"(bhi), "r"(scale_d));
}
__device__ __forceinline__ void mma_ss64(float (&d)[32], uint32_t alo, uint32_t blo, uint32_t bhi, int scale_d) {
  asm volatile("{\n.reg .pred p;\n.reg .b64 da, db;\nsetp.ne.b32 p, %35, 0;\nmov.b64 da, {%32, %36};\nmov.b64 db, {%33, %34};\n"
    "wgmma.mma_async.sync.aligned.m64n64k16.f32.bf16.bf16 {"
    "%0, %1, %2, %3, %4, %5, %6, %7, %8, %9, %10, %11, %12, %13, %14, %15, "
    "%16, %17, %18, %19, %20, %21, %22, %23, %24, %25, %26, %27, %28, %29, %30, %31"
    "}, da, db, p, 1, 1, 0, 1;\n}\n"
    : "+f"(d[0]), "+f"(d[1]), "+f"(d[2]), "+f"(d[3]), "+f"(d[4]), "+f"(d[5]), "+f"(d[6]), "+f"(d[7]),
      "+f"(d[8]), "+f"(d[9]), "+f"(d[10]), "+f"(d[11]), "+f"(d[12]), "+f"(d[13]), "+f"(d[14]), "+f"(d[15]),
      "+f"(d[16]), "+f"(d[17]), "+f"(d[18]), "+f"(d[19]), "+f"(d[20]), "+f"(d[21]), "+f"(d[22]), "+f"(d[23]),
      "+f"(d[24]), "+f"(d[25]), "+f"(d[26]), "+f"(d[27]), "+f"(d[28]), "+f"(d[29]), "+f"(d[30]), "+f"(d[31])
    : "r"(alo), "r"(blo), "r"(bhi), "r"(scale_d), "r"(DESC_HI));
}
__device__ __forceinline__ void mma_s(float (&d)[32], uint32_t alo, uint32_t blo, uint32_t bhi, int scale_d) {
  asm volatile("{\n.reg .pred p;\n.reg .b64 da, db;\nsetp.ne.b32 p, %35, 0;\nmov.b64 da, {%32, %36};\nmov.b64 db, {%33, %34};\n"
    "wgmma.mma_async.sync.aligned.m64n64k16.f32.bf16.bf16 {"
    "%0, %1, %2, %3, %4, %5, %6, %7, %8, %9, %10, %11, %12, %13, %14, %15, "
    "%16, %17, %18, %19, %20, %21, %22, %23, %24, %25, %26, %27, %28, %29, %30, %31"
    "}, da, db, p, 1, 1, 0, 0;\n}\n"
    : "+f"(d[0]), "+f"(d[1]), "+f"(d[2]), "+f"(d[3]), "+f"(d[4]), "+f"(d[5]), "+f"(d[6]), "+f"(d[7]),
      "+f"(d[8]), "+f"(d[9]), "+f"(d[10]), "+f"(d[11]), "+f"(d[12]), "+f"(d[13]), "+f"(d[14]), "+f"(d[15]),
      "+f"(d[16]), "+f"(d[17]), "+f"(d[18]), "+f"(d[19]), "+f"(d[20]), "+f"(d[21]), "+f"(d[22]), "+f"(d[23]),
      "+f"(d[24]), "+f"(d[25]), "+f"(d[26]), "+f"(d[27]), "+f"(d[28]), "+f"(d[29]), "+f"(d[30]), "+f"(d[31])
    : "r"(alo), "r"(blo), "r"(bhi), "r"(scale_d), "r"(DESC_HI));
}
__device__ __forceinline__ void mma_s0(float (&d)[32], uint32_t alo, uint32_t blo, uint32_t bhi) {
  asm volatile("{\n.reg .pred p;\n.reg .b64 da, db;\nsetp.ne.b32 p, %35, 0;\nmov.b64 da, {%32, %36};\nmov.b64 db, {%33, %34};\n"
    "wgmma.mma_async.sync.aligned.m64n64k16.f32.bf16.bf16 {"
    "%0, %1, %2, %3, %4, %5, %6, %7, %8, %9, %10, %11, %12, %13, %14, %15, "
    "%16, %17, %18, %19, %20, %21, %22, %23, %24, %25, %26, %27, %28, %29, %30, %31"
    "}, da, db, p, 1, 1, 0, 0;\n}\n"
    : "=f"(d[0]), "=f"(d[1]), "=f"(d[2]), "=f"(d[3]), "=f"(d[4]), "=f"(d[5]), "=f"(d[6]), "=f"(d[7]),
      "=f"(d[8]), "=f"(d[9]), "=f"(d[10]), "=f"(d[11]), "=f"(d[12]), "=f"(d[13]), "=f"(d[14]), "=f"(d[15]),
      "=f"(d[16]), "=f"(d[17]), "=f"(d[18]), "=f"(d[19]), "=f"(d[20]), "=f"(d[21]), "=f"(d[22]), "=f"(d[23]),
      "=f"(d[24]), "=f"(d[25]), "=f"(d[26]), "=f"(d[27]), "=f"(d[28]), "=f"(d[29]), "=f"(d[30]), "=f"(d[31])
    : "r"(alo), "r"(blo), "r"(bhi), "n"(0), "r"(DESC_HI));
}
__device__ __forceinline__ void mma_pv(float (&d)[16], uint32_t a0, uint32_t a1, uint32_t a2, uint32_t a3, uint32_t blo, uint32_t bhi, int scale_d) {
  asm volatile("{\n.reg .pred p;\n.reg .b64 db;\nsetp.ne.b32 p, %22, 0;\nmov.b64 db, {%20, %21};\n"
    "wgmma.mma_async.sync.aligned.m64n32k16.f32.bf16.bf16 {"
    "%0, %1, %2, %3, %4, %5, %6, %7, %8, %9, %10, %11, %12, %13, %14, %15"
    "}, {%16, %17, %18, %19}, db, p, 1, 1, 1;\n}\n"
    : "+f"(d[0]), "+f"(d[1]), "+f"(d[2]), "+f"(d[3]), "+f"(d[4]), "+f"(d[5]), "+f"(d[6]), "+f"(d[7]),
      "+f"(d[8]), "+f"(d[9]), "+f"(d[10]), "+f"(d[11]), "+f"(d[12]), "+f"(d[13]), "+f"(d[14]), "+f"(d[15])
    : "r"(a0), "r"(a1), "r"(a2), "r"(a3), "r"(blo), "r"(bhi), "r"(scale_d));
}

__device__ __forceinline__ void store_heads(uint32_t rowaddr, uint32_t lane, const uint32_t (&v)[14], uint32_t pad) {
  const uint32_t q = lane & 3;
  uint32_t o[16];
#pragma unroll
  for (int c = 0; c < 8; c++)
#pragma unroll
    for (int hf = 0; hf < 2; hf++) {
      uint32_t x = c < 7 ? v[2 * c + hf] : pad;
      if ((c & 1) && c < 7) x = q == (7u - c) / 2 ? pad : x;
      if (c >= 2) x = q >= 4u - c / 2 ? v[2 * (c - 1) + hf] : x;
      o[2 * c + hf] = x;
    }
#pragma unroll
  for (int g = 0; g < 4; g++)
    stsm4(rowaddr + (((2 * g + (lane >> 4)) ^ (lane & 7)) << 4), o[4 * g], o[4 * g + 1], o[4 * g + 2], o[4 * g + 3]);
}

constexpr float SM_C = 0.18898223650461361f * 1.4426950408889634f;

struct RowStat {
  float m0, m1;
  float al0, al1;
};

__device__ __forceinline__ void mask_block(float (&s)[32], bool diag, int row, int q) {
  const float NEG = __int_as_float(0xff800000);
  const int t0 = row - 2 * q, t1 = t0 + 8;
#pragma unroll
  for (int g = 0; g < 8; g++) {
    if (((8 * g) <= t0) != diag) s[4 * g] = NEG;
    if (((8 * g + 1) <= t0) != diag) s[4 * g + 1] = NEG;
    if (((8 * g) <= t1) != diag) s[4 * g + 2] = NEG;
    if (((8 * g + 1) <= t1) != diag) s[4 * g + 3] = NEG;
  }
}

__device__ __forceinline__ void update_max(const float (&s)[32], RowStat& r, bool first) {
  const float p0 = first ? __int_as_float(0xff800000) : r.m0, p1 = first ? __int_as_float(0xff800000) : r.m1;
  float a0 = fmaxf(s[0], s[1]), a1 = fmaxf(s[2], s[3]), b0 = fmaxf(s[4], s[5]), b1 = fmaxf(s[6], s[7]);
#pragma unroll
  for (int g = 2; g < 8; g += 2) {
    a0 = fmaxf(a0, fmaxf(s[4 * g], s[4 * g + 1]));
    a1 = fmaxf(a1, fmaxf(s[4 * g + 2], s[4 * g + 3]));
    b0 = fmaxf(b0, fmaxf(s[4 * g + 4], s[4 * g + 5]));
    b1 = fmaxf(b1, fmaxf(s[4 * g + 6], s[4 * g + 7]));
  }
  a0 = fmaxf(fmaxf(a0, b0), p0);
  a1 = fmaxf(fmaxf(a1, b1), p1);
  a0 = fmaxf(a0, __shfl_xor_sync(~0u, a0, 1));
  a1 = fmaxf(a1, __shfl_xor_sync(~0u, a1, 1));
  a0 = fmaxf(a0, __shfl_xor_sync(~0u, a0, 2));
  a1 = fmaxf(a1, __shfl_xor_sync(~0u, a1, 2));
  r.al0 = ex2(p0 - a0);
  r.al1 = ex2(p1 - a1);
  r.m0 = a0;
  r.m1 = a1;
}

__device__ __forceinline__ void exp_shifted(float (&s)[32], float m0, float m1) {
#pragma unroll
  for (int g = 0; g < 8; g++) {
    s[4 * g] = ex2(s[4 * g] - m0);
    s[4 * g + 1] = ex2(s[4 * g + 1] - m0);
    s[4 * g + 2] = ex2(s[4 * g + 2] - m1);
    s[4 * g + 3] = ex2(s[4 * g + 3] - m1);
  }
}
template <int G0, int G1> __device__ __forceinline__ void ex2_groups(float (&s)[32]) {
#pragma unroll
  for (int i = 4 * G0; i < 4 * G1; i++) s[i] = ex2(s[i]);
}
constexpr int GX = 6;

__device__ __forceinline__ void issue_s(float (&s)[32], uint32_t qlo, uint32_t klo) {
  wg_fence();
  mma_s0(s, qlo, klo, DESC_HI);
  mma_s(s, qlo + 2, klo + 2, DESC_HI, 1);
  wg_commit();
  sched_fence();
}
__device__ __forceinline__ void issue_pv(float (&o)[16], const uint32_t (&p)[16], uint32_t vlo, int acc_o) {
  wg_fence();
  mma_pv(o, p[0], p[1], p[2], p[3], vlo, DESC_HI, acc_o);
  mma_pv(o, p[4], p[5], p[6], p[7], vlo + 128, DESC_HI, 1);
  mma_pv(o, p[8], p[9], p[10], p[11], vlo + 256, DESC_HI, 1);
  mma_pv(o, p[12], p[13], p[14], p[15], vlo + 384, DESC_HI, 1);
  wg_commit();
  sched_fence();
}
__device__ __forceinline__ void issue_s_pv(float (&s)[32], uint32_t qlo, uint32_t klo, float (&o)[16], const uint32_t (&p)[16],
                                           uint32_t vlo, int acc_o) {
  wg_fence();
  mma_pv(o, p[0], p[1], p[2], p[3], vlo, DESC_HI, acc_o);
  mma_pv(o, p[4], p[5], p[6], p[7], vlo + 128, DESC_HI, 1);
  mma_pv(o, p[8], p[9], p[10], p[11], vlo + 256, DESC_HI, 1);
  mma_pv(o, p[12], p[13], p[14], p[15], vlo + 384, DESC_HI, 1);
  mma_s0(s, qlo, klo, DESC_HI);
  mma_s(s, qlo + 2, klo + 2, DESC_HI, 1);
  wg_commit();
  sched_fence();
}
__device__ __forceinline__ float rcp_fast(float x) {
  float y;
  asm("rcp.approx.ftz.f32 %0, %1;" : "=f"(y) : "f"(x));
  return y;
}
__device__ __forceinline__ void pack_p(const float (&s)[32], uint32_t (&p)[16]) {
#pragma unroll
  for (int i = 0; i < 16; i++) p[i] = pack_bf16(s[2 * i], s[2 * i + 1]);
}
struct PMask { uint32_t d[4], t[3]; };
__device__ __forceinline__ void and_xor(uint32_t& p, uint32_t m, uint32_t inv) {
  asm("lop3.b32 %0, %0, %1, %2, 0x60;" : "+r"(p) : "r"(m), "r"(inv));
}
__device__ __forceinline__ void mask_p(uint32_t (&p)[16], const PMask& mk, uint32_t inv) {
#pragma unroll
  for (int k = 0; k < 4; k++) {
    and_xor(p[4 * k], mk.d[k], inv);
    and_xor(p[4 * k + 1], k == 0 ? ~0u : mk.t[k - 1], inv);
    and_xor(p[4 * k + 2], k == 3 ? 0u : mk.t[k], inv);
    and_xor(p[4 * k + 3], mk.d[k], inv);
  }
}

template <int NG, int N>
__device__ __forceinline__ void glu_group(uint32_t* h, const float (&acc)[N], int g, float a0, float a1) {
  const float* gt = acc + 4 * g;
  const float* up = acc + 4 * (NG + g);
  const float u0 = a0 * up[0], u1 = a0 * up[1], u2 = a1 * up[2], u3 = a1 * up[3];
  h[2 * g] = pack_bf16(fmaf(u0, tanh_fast(0.5f * gt[0]), u0), fmaf(u1, tanh_fast(0.5f * gt[1]), u1));
  h[2 * g + 1] = pack_bf16(fmaf(u2, tanh_fast(0.5f * gt[2]), u2), fmaf(u3, tanh_fast(0.5f * gt[3]), u3));
  asm volatile("" : "+r"(h[2 * g]), "+r"(h[2 * g + 1])::"memory");
}

template <int IT0, int HS0, class Side>
__device__ __forceinline__ void pass64(float (&acc)[64], uint32_t xlo, bool lane0, Side side) {
#pragma unroll
  for (int hs = HS0; hs < 14; hs++) {
    const int st = hs >> 1, k = (hs & 1) * 2;
    const int slot = (IT0 + st) % NSLOT, ph = ((IT0 + st) / NSLOT) & 1;
    const uint32_t a = xlo + st * 1024 + 2 * k, b = desc_lo(OFF_RING + slot * 16384, 8192) + 128 * k;
    if (!(hs & 1)) mbar_wait(B_FULL + 8 * slot, ph);
    wg_fence();
    mma_n128(acc, a, b, DESC_HI, hs != 0);
    mma_n128(acc, a + 2, b + 128, DESC_HI, 1);
    wg_commit();
    sched_fence();
    side(hs);
    sched_fence();
    wg_wait<0>();
    if (hs & 1) mbar_arrive_if(lane0, B_EMPTY + 8 * slot);
  }
  reg_fence(acc);
}

template <int IT0, class Side>
__device__ __forceinline__ void pass32(float (&acc)[32], uint32_t xlo, bool lane0, Side side) {
#pragma unroll
  for (int hs = 0; hs < 7; hs++) {
    const int st = hs >> 1;
    const int slot = (IT0 + st) % NSLOT, ph = ((IT0 + st) / NSLOT) & 1;
    const uint32_t a = xlo + hs * 1024, b = desc_lo(OFF_RING + slot * 16384, 4096) + (hs & 1) * 512;
    if (!(hs & 1)) mbar_wait(B_FULL + 8 * slot, ph);
    wg_fence();
#pragma unroll
    for (int k = 0; k < 4; k++) mma_ss64(acc, a + 2 * k, b + 64 * k, DESC_HI64, (hs | k) != 0);
    wg_commit();
    sched_fence();
    side(hs);
    sched_fence();
    wg_wait<0>();
    if ((hs & 1) || hs == 6) mbar_arrive_if(lane0, B_EMPTY + 8 * slot);
  }
  reg_fence(acc);
}

struct Ring {
  uint32_t slot, phase;
  __device__ __forceinline__ void next() {
    if (++slot == NSLOT) { slot = 0; phase ^= 1; }
  }
};

__global__ void __cluster_dims__(2, 1, 1) __launch_bounds__(512, 1)
fused_kernel(const uint8_t* __restrict__ x, const __nv_bfloat16* __restrict__ gate_w,
             __nv_bfloat16* __restrict__ out, const __grid_constant__ Maps maps) {
  const int warp = __shfl_sync(~0u, (int)(threadIdx.x >> 5), 0);
  const int wg = warp >> 2;
  const int lane = threadIdx.x & 31;
  const int cl = blockIdx.x >> 1, rank = blockIdx.x & 1;
  const int pos = cl < 36 ? (cl - 4) & 7 : (cl - 36) % 7;
  const int blk = cl < 4 ? 0 : (cl < 36 ? (pos < 2 ? 1 - pos : pos) : pos + 1);
  const int k8 = cl < 4 ? cl : (cl < 36 ? ((cl - 4) >> 3) + (blk == 0 ? 4 : 0) : 4 + (cl - 36) / 7);
  const int cta = (((blk >> 1) * 4 + (k8 >> 1)) * 8 + (blk & 1) * 4 + (k8 & 1) * 2 + rank) & 127, m = cta >> 3, j = cta & 7;
  const int wcol = 56 * j - 8 * (j & 1);

  if (wg == 2) {
    const uint32_t t = threadIdx.x & 127, r0 = t >> 3, ch = t & 7;
    const uint8_t* src = x + (size_t)(m * 128 + r0) * 896 + ch * 16;
    const uint32_t dst = OFF_X + r0 * 128 + ((ch ^ (r0 & 7)) << 4);
#pragma unroll
    for (int c = 0; c < 2; c++) {
#pragma unroll
      for (int i = 0; i < 8; i++)
        asm volatile("cp.async.cg.shared.global [%0], [%1], 16;" ::"r"(self(dst + c * 16384 + i * 2048)), "l"(src + c * 128 + i * 16 * 896) : "memory");
      asm volatile("cp.async.commit_group;" ::: "memory");
    }
  } else if (warp == 12) {
    if (elect_one()) {
      TS(0);
#pragma unroll
      for (int i = 0; i < 4; i++) mbar_init(B_EFULL + 8 * i, 1);
      TS(40);
#pragma unroll
      for (int s = 0; s < 4; s++) {
        mbar_expect_tx(B_EFULL + 8 * s, 12288);
        tma3d(OFF_E + s * 12288, &maps.qkv, wcol, 32 * s, 0, B_EFULL + 8 * s);
      }
      TS(42);
    }
  } else if (warp == 13) {
    if (elect_one()) {
      if ((smem_u32(smem_raw) & 0xFFFFFFu) != SB) __trap();
#pragma unroll
      for (uint32_t b = B_FULL; b < B_EMPTY; b += 8) mbar_init(b, 1);
#pragma unroll
      for (int c = 0; c < 6; c++) mbar_expect_tx(B_LFULL + 8 * c, 8192);
    }
  } else if (warp == 15) {
    if (elect_one()) {
#pragma unroll
      for (uint32_t b = B_EMPTY; b < B_END; b += 8)
        mbar_init(b, b < B_XFULL ? 8 : 4);
    }
  } else if (warp == 14) {
    const uint8_t* gw = reinterpret_cast<const uint8_t*>(gate_w) + lane * 16;
    asm volatile("cp.async.cg.shared.global [%0], [%1], 16;" ::"r"(self(OFF_GW + lane * 16)), "l"(gw) : "memory");
    if (lane < 24) asm volatile("cp.async.cg.shared.global [%0], [%1], 16;" ::"r"(self(OFF_GW + 512 + lane * 16)), "l"(gw + 512) : "memory");
    asm volatile("cp.async.commit_group;" ::: "memory");
  }
  __syncthreads();

  if (wg == 3) {
    auto patch_gate = [&](int s0, int s1) {
      const uint32_t prow = lane + (j & 1), poff = prow * 128 + ((((j & 1) ? 0 : 7) ^ (prow & 7)) << 4);
#pragma unroll 1
      for (int s = s0; s < s1; s++) {
        unsigned short v;
        asm volatile("ld.shared.u16 %0, [%1];" : "=h"(v) : "r"(self(OFF_GW + s * 64 + lane * 2)) : "memory");
        for (uint32_t it = 0; !mbar_try(((s & 4) ? B_FULL : B_EFULL) + 8 * (s & 3), s >> 3); it++)
          if (it > (POLL_LIMIT << 4)) __trap();
        const uint32_t buf = (s & 4) ? OFF_RING + (s & 3) * 16384 : OFF_E + (s & 3) * 12288;
        asm volatile("st.shared.u16 [%0], %1;" ::"r"(self(buf + poff)), "h"(v) : "memory");
        __syncwarp();
        mbar_arrive_if(lane == 0, B_GW + 8 * s);
      }
    };
    if (warp == 12) {
      if (elect_one()) {
#pragma unroll 1
        for (int s = 4; s < 8; s++) {
          mbar_expect_tx(B_FULL + 8 * (s - 4), 12288);
          tma3d(OFF_RING + (s - 4) * 16384, &maps.qkv, wcol, 32 * s, 0, B_FULL + 8 * (s - 4));
        }
      }
    } else if (warp == 14) {
      asm volatile("cp.async.wait_group 0;" ::: "memory");
      __syncwarp();
      patch_gate(0, 2);
    }
    __syncwarp();
    asm volatile("setmaxnreg.dec.sync.aligned.u32 24;");
    auto ship = [&](int w) {
      const uint32_t peer = in_cta(SB, rank ^ 1) - SB;
      mbar_wait(B_ZOK, 0);
      fence_async_global();
      mbar_wait(B_GO + 8, 0);
#pragma unroll 1
      for (int p = 0; p < 7; p++) {
        const uint32_t tile = g2_tile(p, w);
        const int col = g2_col(p, rank);
        mbar_wait(B_OUT + 16 * p + 8 * w, 0);
        fence_async_smem();
        if ((p & 1) || p == 6) {
          asm volatile("cp.reduce.async.bulk.tensor.2d.global.shared::cta.add.tile.bulk_group [%0, {%2, %3}], [%1];"
                       ::"l"(&maps.out), "r"(self(tile)), "r"(col), "r"(m * 128 + w * 64) : "memory");
        } else {
          asm volatile("cp.async.bulk.shared::cluster.shared::cta.mbarrier::complete_tx::bytes [%0], [%1], 8192, [%2];"
                       ::"r"(peer + out_tile(p + w)), "r"(self(tile)), "r"(peer + B_LFULL + 8 * (p + w)) : "memory");
        }
      }
      asm volatile("cp.async.bulk.commit_group;" ::: "memory");
      asm volatile("cp.async.bulk.wait_group.read 0;" ::: "memory");
      mbar_wait(B_RCVD, 0);
      TS(21 + w);
    };
    if (warp == 12) {
      if (!elect_one()) return;
      const int f0 = 224 * j;
      const int fh = (j & 1) ? f0 : f0 + 192;
      const int ff = (j & 1) ? f0 + 32 : f0;
      Ring r{0, 0};
#pragma unroll 1
      for (int s = 8; s < 14; s++) {
        if (s & 4) {
          mbar_wait(B_EMPTY + 8 * r.slot, r.phase);
          mbar_expect_tx(B_FULL + 8 * r.slot, 12288);
          tma3d(OFF_RING + r.slot * 16384, &maps.qkv, wcol, 32 * s, 0, B_FULL + 8 * r.slot);
          r.next();
        } else {
          const int e = s & 3;
          mbar_wait(B_EEMPTY + 8 * e, 0);
          mbar_expect_tx(B_EFULL + 8 * e, 12288);
          tma3d(OFF_E + e * 12288, &maps.qkv, wcol, 32 * s, 0, B_EFULL + 8 * e);
        }
      }
#pragma unroll 1
      for (int ps = 0; ps < 3; ps++) {
        if (ps == 2) {
#pragma unroll 1
          for (int s = 0; s < 4; s++) {
            const uint32_t fb = B_FULL + 8 * r.slot, dst = OFF_RING + r.slot * 16384;
            mbar_wait(B_EMPTY + 8 * r.slot, r.phase);
            mbar_expect_tx(fb, s < 3 ? 16384 : 8192);
            tma2d(dst, &maps.g32, fh, 128 * s, fb);
            tma2d(dst + 4096, &maps.u32, fh, 128 * s, fb);
            if (s < 3) {
              tma2d(dst + 8192, &maps.g32, fh, 128 * s + 64, fb);
              tma2d(dst + 12288, &maps.u32, fh, 128 * s + 64, fb);
            }
            r.next();
          }
        }
#pragma unroll 1
        for (int s = 0; s < 7; s++) {
          const uint32_t fb = B_FULL + 8 * r.slot, dst = OFF_RING + r.slot * 16384;
          mbar_wait(B_EMPTY + 8 * r.slot, r.phase);
          mbar_expect_tx(fb, 16384);
          tma2d(dst, &maps.g64, ff + 64 * ps, 64 * s, fb);
          tma2d(dst + 8192, &maps.u64, ff + 64 * ps, 64 * s, fb);
          r.next();
        }
      }
      uint32_t gb = 0;
#pragma unroll 1
      for (int c = 0; c < 7; c++) {
        if (c >= 3) {
          mbar_wait(B_GEMPTY + 8 * gb, c >= 6);
        } else if (c > 0) {
#pragma unroll 1
          for (int i = 0; i < 2; i++) {
            mbar_wait(B_EMPTY + 8 * r.slot, r.phase);
            r.next();
          }
          if (c == 2) {
            mbar_arrive(B_GO);
            mbar_wait(B_ZOK, 0);
            asm volatile("mbarrier.arrive.shared::cluster.b64 _, [%0];" ::"r"(in_cta(B_GO + 8, rank ^ 1)) : "memory");
          }
        }
        const uint32_t fb = B_GFULL + 8 * gb, dst = g2_buf(gb);
        mbar_expect_tx(fb, G2_BYTES);
        const int col = g2_col(c, rank);
        tma2d(dst, &maps.down64, col, ff, fb);
        tma2d(dst + 8192, &maps.down64, col, ff + 64, fb);
        tma2d(dst + 16384, &maps.down, col, fh, fb);
        tma2d(dst + 20480, &maps.down64, col, ff + 128, fb);
        tma2d(dst + 28672, &maps.wo, col, 56 * j, fb);
        gb = gb == 2 ? 0 : gb + 1;
      }
    } else if (warp == 13) {
      const uint32_t b = cta;
      mbar_wait(B_EPOCH, 0);
      const unsigned epoch = __float_as_uint(lds_f32(OFF_EPOCH));
      const int back = lane < 2 ? lane + 1 : 0;
      const unsigned* flag = &g_ex[m >= back ? b - 8 * back : b].flag;
      const int nB = min(5, 2 * m + 2), nsteps = nB + min(5, 2 * m + 1);
      auto key_block = [&](int n) { return n < nB ? 2 * m + 1 - (nB == 5 && n >= 3 ? 7 - n : n) : 2 * m + nB - n; };
      mbar_wait(B_K1RDY, 0);
      const int settle = epoch == 1 ? 1 : nsteps;
      int seen = 0;
#pragma unroll 1
      for (int n = 1; n <= nsteps; n++) {
        if (n == settle) {
          if (lane < 3) flag_wait(flag, epoch * 8 + 5);
          __syncwarp();
          fence_async_global();
          mbar_arrive_if(lane == 0, B_SETTLED);
        }
        if (n == nsteps) break;
        const int kv = key_block(n), kk = key_block(n + 1);
        const uint32_t fb = B_KVFULL + 8 * (n & 1);
        if (n < settle) {
          const int need = lane == 0 ? (m >= 2 || n == 1 ? min(n, 4) : min(n + 1, 4)) : (m < 2 ? 0 : (n < 4 ? n - 1 : (n < 7 ? 2 : 4)));
#pragma unroll 1
          for (uint32_t it = 0; __any_sync(~0u, lane < 2 && need && seen < need); it++) {
            unsigned v;
            asm volatile("ld.relaxed.gpu.global.u32 %0, [%1];" : "=r"(v) : "l"(flag) : "memory");
            seen = v - epoch * 8;
            if (it > POLL_LIMIT) __trap();
          }
          if (n < 4) mbar_wait(B_PUB + 8 * (m > 0 ? n - 1 : 2), 0);
          __syncwarp();
          if (n < 3) TS(22 + n);
        }
        mbar_wait(B_KVEMPTY + 8 * ((n - 1) & 1), ((n - 1) >> 1) & 1);
        if (elect_one()) {
          mbar_expect_tx(fb, (n == 1 || n + 1 == nsteps) ? 8192 : 16384);
          if (n + 1 < nsteps) bulk_load(OFF_KV + ((n + 1) & 1) * 16384, kv_block(kk, j), 8192, fb);
          if (n > 1) bulk_load(OFF_KV + (n & 1) * 16384 + 8192, kv_block(kv, j) + 8192, 8192, fb);
        }
      }
      if (!elect_one()) return;
      ship(0);
    } else {
      if (warp == 14) {
        patch_gate(2, 14);
        mbar_wait(B_PUB + 16, 0);
        uint4* z = reinterpret_cast<uint4*>(out + (size_t)(m * 128 + j * 16) * 448);
#pragma unroll 4
        for (int i = 0; i < 28; i++) z[lane + i * 32] = make_uint4(0, 0, 0, 0);
        __syncwarp();
        mbar_arrive_if(lane < 4, B_ZRDY);
        return;
      }
      if (!elect_one()) return;
      mbar_wait(B_XFULL + 8 * 2, 0);
      const unsigned epoch = *(volatile unsigned*)&g_ex[cta].epoch + 1;
      sts32(OFF_EPOCH, epoch);
      mbar_arrive(B_EPOCH);
      *(volatile unsigned*)&g_ex[cta].epoch = epoch;
#pragma unroll 1
      for (int i = 0; i < 4; i++) {
        mbar_wait(i == 0 ? B_K1RDY : B_VRDY, 0);
        fence_async_smem();
        uint8_t* dst = g_ex[cta].kv[1 - (i >> 1)] + (i & 1) * 8192;
        asm volatile("cp.async.bulk.global.shared::cta.bulk_group [%0], [%1], 8192;" ::"l"(dst), "r"(self(OFF_KV + i * 8192)) : "memory");
        asm volatile("cp.async.bulk.commit_group;" ::: "memory");
        for (const uint32_t t0 = clock(); clock() - t0 < 300;) {}
        asm volatile("st.relaxed.gpu.global.u32 [%0], %1;" ::"l"(&g_ex[cta].flag), "r"(epoch * 8 + 1 + i) : "memory");
        asm volatile("cp.async.bulk.wait_group 0;" ::: "memory");
        if (i != 1) mbar_arrive(B_PUB + 8 * (i == 0 ? 0 : i - 1));
        if (i == 0) TS(25);
      }
      asm volatile("st.release.gpu.global.u32 [%0], %1;" ::"l"(&g_ex[cta].flag), "r"(epoch * 8 + 5) : "memory");
      TS(26);
      mbar_wait(B_ZRDY, 0);
      asm volatile("red.release.gpu.global.add.u32 [%0], 1;" ::"l"(&g_zflag[m * 8]) : "memory");
      flag_wait(&g_zflag[m * 8], epoch * 8);
      mbar_arrive(B_ZOK);
      ship(1);
    }
  } else if (wg == 2) {
    const int t = threadIdx.x & 127;
    const bool lane0 = lane == 0;
    {
      const uint32_t r0 = t >> 3, ch = t & 7;
      const uint8_t* src = x + (size_t)(m * 128 + r0) * 896 + ch * 16;
      const uint32_t dst = OFF_X + r0 * 128 + ((ch ^ (r0 & 7)) << 4);
#pragma unroll 1
      for (int c = 2; c < 7 + XAHEAD; c++) {
        if (c < 7) {
#pragma unroll
          for (int i = 0; i < 8; i++)
            asm volatile("cp.async.cg.shared.global [%0], [%1], 16;" ::"r"(self(dst + c * 16384 + i * 2048)), "l"(src + c * 128 + i * 16 * 896) : "memory");
        }
        asm volatile("cp.async.commit_group;" ::: "memory");
        if (c >= XAHEAD) {
          asm volatile("cp.async.wait_group %0;" ::"n"(XAHEAD) : "memory");
          fence_async_smem();
          __syncwarp();
          mbar_arrive_if(lane0, B_XFULL + 8 * (c - XAHEAD));
          TS(33 + c - XAHEAD);
        }
      }
    }
    asm volatile("setmaxnreg.inc.sync.aligned.u32 152;");
    const int wi = warp & 3, q = lane & 3;
    const int row = wi * 16 + (lane >> 2);
    constexpr uint32_t QLO = desc_lo(OFF_QO, 16), KVLO = desc_lo(OFF_KV, 16);
    float sa[32], sb[32], o0[16], o1[16];
    uint32_t p[16];
    bool odd = false;
    float g0 = 0.f, g1 = 0.f;
    auto load_gate = [&](int w) {
      mbar_wait(B_GRDY, 0);
      g0 = lds_f32(OFF_G + (w * 64 + row) * 4);
      g1 = lds_f32(OFF_G + (w * 64 + row + 8) * 4);
    };
    auto finalize = [&](int w, bool check) -> bool {
      const float l00 = __shfl_sync(~0u, odd ? o0[5] : o0[4], lane | 3), l01 = __shfl_sync(~0u, odd ? o0[7] : o0[6], lane | 3);
      const float l10 = __shfl_sync(~0u, odd ? o1[13] : o1[12], lane & ~3), l11 = __shfl_sync(~0u, odd ? o1[15] : o1[14], lane & ~3);
      if (check) {
        uint32_t d[4];
#pragma unroll
        for (int i = 0; i < 4; i++) {
          const float* o = (i < 2 ? o0 : o1) + 4 + 8 * (i & 1);
          const uint32_t e = __float_as_uint(o[0]) | __float_as_uint(o[2]), f = __float_as_uint(o[1]) | __float_as_uint(o[3]);
          d[i] = odd ? e : f;
        }
        const uint32_t da = (q & 1) ? d[0] : d[1], db = (q & 1) ? d[2] : d[3];
        const uint32_t dd = (q & 2) ? da : db;
        const float lo = fminf(fminf(l00, l01), fminf(l10, l11)), hi = l00 + l01 + l10 + l11;
        if (!__all_sync(~0u, (dd << 1) == 0 && lo >= 0x1p-100f && hi <= 0x1p100f)) return false;
      }
      const float i00 = g0 * rcp_fast(l00), i01 = g1 * rcp_fast(l01);
      const float i10 = g0 * rcp_fast(l10), i11 = g1 * rcp_fast(l11);
      uint32_t v[16];
#pragma unroll
      for (int g = 0; g < 4; g++) {
        v[2 * g] = pack_bf16(o0[4 * g] * i00, o0[4 * g + 1] * i00);
        v[2 * g + 1] = pack_bf16(o0[4 * g + 2] * i01, o0[4 * g + 3] * i01);
        v[8 + 2 * g] = pack_bf16(o1[4 * g] * i10, o1[4 * g + 1] * i10);
        v[8 + 2 * g + 1] = pack_bf16(o1[4 * g + 2] * i11, o1[4 * g + 3] * i11);
      }
#pragma unroll
      for (int g = 0; g < 4; g++) sts128(OFF_QO + w * 8192 + wi * 2048 + g * 512 + lane * 16, v[4 * g], v[4 * g + 1], v[4 * g + 2], v[4 * g + 3]);
      __syncwarp();
      mbar_arrive_if(lane0, B_ORDY + 8 * w);
      TS(31 + w);
      return true;
    };
    const uint32_t tri = ((2 * q <= (lane >> 2)) ? 0xffffu : 0u) | ((2 * q + 1 <= (lane >> 2)) ? 0xffff0000u : 0u);
    PMask mk;
#pragma unroll
    for (int k = 0; k < 4; k++) {
      mk.d[k] = k == wi ? tri : (k < wi ? ~0u : 0u);
      asm volatile("" : "+r"(mk.d[k]));
      if (k < 3) {
        mk.t[k] = k < wi ? ~0u : 0u;
        asm volatile("" : "+r"(mk.t[k]));
      }
    }
#pragma unroll
    for (int i = 0; i < 16; i++) p[i] = 0u;
    mbar_wait(B_QKRDY + 8, 0);
    fence_async_smem();
    odd = __float_as_uint(lds_f32(OFF_EPOCH)) & 1;
    TS(30);
    issue_s(sa, QLO + 512, KVLO);
    wg_wait<0>();
    reg_fence(sa);
    uint32_t ctl = m >= 2 ? 012000142001u : (m == 1 ? 010014001u : 01141u);
    asm volatile("" : "+r"(ctl));
    uint32_t qd = QLO + 512;
    uint32_t kd = KVLO, kp = KVLO - 512;
    int acc_prev = 0;
    uint32_t redo = 0;
    uint32_t gbar = B_VRDY, gpar = 0, ebar = B_KVEMPTY;
    int n = 0;
#pragma unroll 1
    do {
      TA(0);
      issue_s_pv(sb, qd + 4, kd + 4, o1, p, kp + 512 + 4, acc_prev);
      TA(1);
      ex2_groups<0, GX>(sa);
      reg_fence(sa);
      const uint32_t landed = mbar_try(gbar, gpar);
      uint32_t qn = (ctl & 4) ? QLO : qd;
      uint32_t kn = (ctl >> 3) != 1 ? kd ^ 1024 : kd + 512;
      uint32_t inv = (ctl & 2) ? ~0u : 0u;
      acc_prev = !(ctl & 1);
      asm volatile("" : "+r"(qn), "+r"(kn), "+r"(inv), "+r"(acc_prev));
      sched_fence();
      TA(2);
      wg_wait<0>();
      TA(3);
      reg_fence(o1);
      reg_fence(p);
      reg_fence(sb);
      mbar_arrive_if(lane0, ebar);
      ex2_groups<GX, 8>(sa);
      pack_p(sa, p);
      if (ctl & 3) {
        mask_p(p, mk, inv);
        if (ctl & 1) {
          if (qd != QLO) {
            mbar_wait(B_VRDY, 0);
            fence_async_smem();
          } else if (!finalize(1, true)) {
            redo = 2;
          }
        }
      }
      TA(4);
      if (!landed) mbar_wait(gbar, gpar);
      TA(5);
      issue_s_pv(sa, qn, kn, o0, p, kd + 512, acc_prev);
      TA(6);
      ex2_groups<0, GX>(sb);
      reg_fence(sb);
      gbar = B_KVFULL + 8 * ((n + 1) & 1);
      gpar = (n >> 1) & 1;
      ebar ^= 8;
      kp = kd;
      kd ^= 1024;
      asm volatile("" : "+r"(gbar), "+r"(gpar), "+r"(ebar), "+r"(kp), "+r"(kd));
      sched_fence();
      wg_wait<0>();
      sched_fence();
      TA(7);
      reg_fence(o0);
      reg_fence(p);
      reg_fence(sa);
      ex2_groups<GX, 8>(sb);
      pack_p(sb, p);
      if (ctl & 3) {
        mask_p(p, mk, inv);
        if (ctl & 1) load_gate(qd != QLO);
      }
      qd = qn;
      ctl >>= 3;
      TS(44 + n);
      n++;
    } while (ctl != 1);
    issue_pv(o1, p, kp + 512 + 4, acc_prev);
    wg_wait<0>();
    reg_fence(o1);
    reg_fence(p);
    if (!finalize(0, true)) redo |= 1;
    uint32_t any;
    asm volatile("{\n.reg .pred p, q;\nsetp.ne.u32 p, %1, 0;\nbar.red.or.pred q, 1, 128, p;\nselp.u32 %0, 1, 0, q;\n}"
                 : "=r"(any) : "r"(redo) : "memory");
    if (any) {
      uint32_t ph = 0;
      RowStat r0{}, r1{};
      mbar_wait(B_SETTLED, 0);
#pragma unroll 1
      for (int w = 0; w < 2; w++) {
        const int cnt = min(5, 2 * m + 1 + w);
#pragma unroll 1
        for (int t = 0; t < cnt; t++) {
          asm volatile("bar.sync 1, 128;" ::: "memory");
          if (wi == 0 && elect_one()) {
            fence_async_global();
            mbar_expect_tx(B_SLOW, 16384);
            bulk_load(OFF_KV, kv_block(2 * m + w - t, j), 16384, B_SLOW);
          }
          mbar_wait(B_SLOW, ph);
          ph ^= 1;
          auto head = [&](float (&o)[16], RowStat& r, uint32_t hoff) {
            issue_s(sa, QLO + w * 512 + hoff, KVLO + hoff);
            wg_wait<0>();
            reg_fence(sa);
            if ((t & 3) == 0) mask_block(sa, t == 0, row, q);
            update_max(sa, r, t == 0);
            exp_shifted(sa, r.m0, r.m1);
            pack_p(sa, p);
#pragma unroll
            for (int g = 0; g < 4; g++) {
              o[4 * g] *= r.al0; o[4 * g + 1] *= r.al0; o[4 * g + 2] *= r.al1; o[4 * g + 3] *= r.al1;
            }
            issue_pv(o, p, KVLO + 512 + hoff, t != 0);
            wg_wait<0>();
            reg_fence(o);
            reg_fence(p);
          };
          head(o0, r0, 0);
          head(o1, r1, 4);
        }
        if ((redo >> w) & 1) {
          load_gate(w);
          finalize(w, false);
        }
      }
    }
    mbar_arrive_if(lane0, B_ATTDONE);
  } else {
    const int w = wg, wi = warp & 3, q = lane & 3;
    const bool lane0 = lane == 0;
    const int row = wi * 16 + (lane >> 2);
    const uint32_t xlo = desc_lo(OFF_X, 16) + w * 512;
    float acc[92];
    uint32_t vp[14], sh;
    const uint32_t srow = (wi * 16 + (lane & 7) + ((lane >> 3) & 1) * 8) * 128;
    {
      uint32_t prev = 0;
#pragma unroll
      for (int s = 0; s < 14; s++) {
        if (!(s & 1)) mbar_wait(B_XFULL + 4 * s, 0);
        const bool ring = s & 4;
        const uint32_t sl = s & 3;
        const uint32_t a = xlo + (s >> 1) * 1024 + (s & 1) * 4;
        const uint32_t b = (ring ? desc_lo(OFF_RING, 4096) + sl * 1024 : desc_lo(OFF_E, 4096) + sl * 768) + (j & 1);
        mbar_wait(B_GW + 8 * s, 0);
        fence_async_smem();
        if (s == 0) TS(1 + w);
        wg_fence();
        mma_qkv(acc, a, b, DESC_HI, s);
        mma_qkv(acc, a + 2, b + 128, DESC_HI, 1);
        wg_commit();
        wg_wait<1>();
        mbar_arrive_if(lane0 && s > 0, prev);
        if (s == 6) asm volatile("setmaxnreg.inc.sync.aligned.u32 168;");
        prev = (ring ? B_EMPTY : B_EEMPTY) + 8 * sl;
      }
      mbar_wait(B_EPOCH, 0);
      sh = (__float_as_uint(lds_f32(OFF_EPOCH)) & 1) * 16;
      mbar_wait(B_EEMPTY + 8 * 3, 1);
      wg_wait<0>();
      mbar_arrive_if(lane0, prev);
      reg_fence(acc);
      TS(3 + w);
    }
    uint32_t h[72];
    float a0, a1;
    float accA[64], accB[64], accH[32], accC[64];
    {
      const uint32_t kvt = OFF_KV + (1 - w) * 16384 + srow;
      {
        uint32_t v[14];
#pragma unroll
        for (int i = 0; i < 14; i++) v[i] = pack_bf16(acc[32 + 2 * i], acc[32 + 2 * i + 1]);
        store_heads(kvt, lane, v, 0x3F80u << sh);
        if (w == 1) {
          __syncwarp();
          mbar_arrive_if(lane0, B_K1RDY);
        }
      }
      {
        uint32_t v[14];
#pragma unroll
        for (int i = 0; i < 14; i++) v[i] = pack_bf16(acc[2 * i] * SM_C, acc[2 * i + 1] * SM_C);
        store_heads(OFF_QO + w * 8192 + srow, lane, v, 0x71800000u >> sh);
      }
      __syncwarp();
      mbar_arrive_if(lane0, B_QKRDY + 8 * w);
      TS(5 + w);
#pragma unroll
      for (int i = 0; i < 14; i++) vp[i] = pack_bf16(acc[64 + 2 * i], acc[64 + 2 * i + 1]);
      reg_fence(vp);
    }
    uint32_t vpad;
    pass64<IT_P1, 0>(accA, xlo, lane0, [&](int hs) {
      if (hs == 0) {
        uint32_t big = 0;
#pragma unroll
        for (int i = 0; i < 14; i += 2) big = __vimax3_u16x2(big, vp[i] & 0x7fff7fffu, vp[i + 1] & 0x7fff7fffu);
        vpad = __any_sync(~0u, max(big >> 16, big & 0xffffu) >= 0x4980u) ? 0x3F803F80u : 0x3F80u << sh;
        asm volatile("" : "+r"(vpad));
      }
      if (hs == 1) {
        store_heads(OFF_KV + (1 - w) * 16384 + 8192 + srow, lane, vp, vpad);
        __syncwarp();
        mbar_arrive_if(lane0, B_VRDY);
        TS(27 + w);
      }
      if (hs == 2) {
        a0 = __expf(-__shfl_sync(~0u, acc[28], lane & ~3));
        a1 = __expf(-__shfl_sync(~0u, acc[30], lane & ~3));
        asm volatile("" : "+f"(a0), "+f"(a1));
      }
      if (hs == 3) {
        const float g0 = __fdividef(1.f, 1.f + a0), g1 = __fdividef(1.f, 1.f + a1);
        sts32(OFF_G + (w * 64 + row + (q & 1) * 8) * 4, __float_as_uint((q & 1) ? g1 : g0));
        a0 = 0.5f - 0.5f * g0;
        a1 = 0.5f - 0.5f * g1;
        __syncwarp();
        mbar_arrive_if(lane0, B_GRDY);
      }
    });
    TS(7 + w);
    pass64<IT_P2, 0>(accB, xlo, lane0, [&](int hs) { if (!(hs & 1)) glu_group<8>(h, accA, hs >> 1, a0, a1); if (hs == 1) glu_group<8>(h, accA, 7, a0, a1); });
    TS(9 + w);
    pass32<IT_P3>(accH, xlo, lane0, [&](int hs) {
      glu_group<8>(h + 16, accB, hs, a0, a1);
      if (hs == 0) glu_group<8>(h + 16, accB, 7, a0, a1);
    });
    TS(11 + w);
    pass64<IT_P4, 0>(accC, xlo, lane0, [&](int hs) { if (hs < 8 && !(hs & 1)) glu_group<4>(h + 32, accH, hs >> 1, a0, a1); });
    TS(13 + w);
    {
      float acc0[32], acc1[32];
      const uint32_t slot0 = wi * 2048 + ((lane & 7) + ((lane >> 3) & 1) * 8) * 128;
      auto slot = [&](int g) { return slot0 + (((2 * g + (lane >> 4)) ^ (lane & 7)) << 4); };
      auto mma_k = [&](float (&acc)[32], uint32_t b, int k) {
        mma_rs64(acc, h[4 * k], h[4 * k + 1], h[4 * k + 2], h[4 * k + 3], b + k * 128, DESC_HI, k);
      };
      {
        constexpr uint32_t b = desc_lo(g2_buf(0), 4096);
        mbar_wait(B_GFULL, 0);
        wg_fence();
#pragma unroll
        for (int k = 0; k < 6; k++) mma_k(acc0, b, k);
        wg_commit();
        sched_fence();
#pragma unroll
        for (int g = 0; g < 4; g++) glu_group<8>(h + 40, accC, g, a0, a1);
        wg_fence();
#pragma unroll
        for (int k = 6; k < 12; k++) mma_k(acc0, b, k);
        wg_commit();
        sched_fence();
#pragma unroll
        for (int g = 4; g < 8; g++) glu_group<8>(h + 40, accC, g, a0, a1);
        mbar_wait(B_ORDY + 8 * w, 0);
        TS(15 + w);
#pragma unroll
        for (int g = 0; g < 4; g++) {
          const uint4 r = lds128(OFF_QO + w * 8192 + wi * 2048 + g * 512 + lane * 16);
          h[56 + 4 * g] = r.x; h[57 + 4 * g] = r.y; h[58 + 4 * g] = r.z; h[59 + 4 * g] = r.w;
        }
#pragma unroll
        for (int i = 2; i < 14; i++) h[56 + i] = q >= (8 - i / 2) / 2 ? h[58 + i] : h[56 + i];
        h[70] = h[71] = 0u;
        wg_fence();
#pragma unroll
        for (int k = 12; k < 18; k++) mma_k(acc0, b, k);
        wg_commit();
        mbar_wait(B_GO, 0);
      }
      uint32_t gb = 1;
      auto fetch_peer = [&](uint4 (&x)[4], int p) {
        mbar_wait(B_LFULL + 8 * (2 * ((p >> 1) - 1) + w), 0);
#pragma unroll
        for (int g = 0; g < 4; g++) x[g] = lds128(g2_tile(p, w) + slot(g));
      };
      auto stage_sum = [&](const uint32_t (&v)[16], const uint4 (&x)[4], int p) {
#pragma unroll
        for (int g = 0; g < 4; g++)
          stsm4(g2_tile(p, w) + slot(g), add_bf16x2(v[4 * g], x[g].x), add_bf16x2(v[4 * g + 1], x[g].y),
                add_bf16x2(v[4 * g + 2], x[g].z), add_bf16x2(v[4 * g + 3], x[g].w));
        __syncwarp();
        mbar_arrive_if(lane0, B_OUT + 16 * p + 8 * w);
      };
      auto chunk = [&](float (&acc)[32], float (&prv)[32], int c, bool send) {
        const uint32_t b = desc_lo(0, 4096) + (g2_buf(gb) >> 4);
        mbar_wait(B_GFULL + 8 * gb, c >= 3 && c < 6);
        wg_fence();
#pragma unroll
        for (int k = 0; k < G2A; k++) mma_k(acc, b, k);
        wg_commit();
        wg_wait<1>();
        reg_fence(prv);
        mbar_arrive_if(lane0, B_GEMPTY + 8 * (gb == 0 ? 2 : gb - 1));
        uint32_t v[16];
#pragma unroll
        for (int i = 0; i < 16; i++) v[i] = pack_bf16(prv[2 * i], prv[2 * i + 1]);
        if (send) {
          if (c == 3) mbar_wait(B_ATTDONE, 0);
#pragma unroll
          for (int g = 0; g < 4; g++) sts128(g2_tile(c - 1, w) + slot(g), v[4 * g], v[4 * g + 1], v[4 * g + 2], v[4 * g + 3]);
          __syncwarp();
          mbar_arrive_if(lane0, B_OUT + 16 * (c - 1) + 8 * w);
          wg_fence();
#pragma unroll
          for (int k = G2A; k < 18; k++) mma_k(acc, b, k);
          wg_commit();
        } else {
          uint4 x[4] = {};
          reg_fence(v);
          if (c > 2) fetch_peer(x, c - 1);
          wg_fence();
#pragma unroll
          for (int k = G2A; k < G2B; k++) mma_k(acc, b, k);
          wg_commit();
          sched_fence();
          stage_sum(v, x, c - 1);
          wg_fence();
#pragma unroll
          for (int k = G2B; k < 18; k++) mma_k(acc, b, k);
          wg_commit();
        }
        TS((w == 1 ? 53 : 70) + c);
        gb = gb == 2 ? 0 : gb + 1;
      };
#pragma unroll 1
      for (int c = 1; c < 7; c += 2) {
        chunk(acc1, acc0, c, true);
        chunk(acc0, acc1, c + 1, false);
      }
      {
        uint32_t v[16];
        uint4 x[4];
        fetch_peer(x, 6);
        if (lane0) asm volatile("mbarrier.arrive.shared::cluster.b64 _, [%0];" ::"r"(in_cta(B_RCVD, rank ^ 1)) : "memory");
        sched_fence();
        wg_wait<0>();
        TS(17 + w);
        reg_fence(acc0);
#pragma unroll
        for (int i = 0; i < 16; i++) v[i] = pack_bf16(acc0[2 * i], acc0[2 * i + 1]);
        stage_sum(v, x, 6);
      }
    }
  }
}

typedef CUresult (*EncodeFn)(CUtensorMap*, CUtensorMapDataType, cuuint32_t, void*, const cuuint64_t*, const cuuint64_t*,
                             const cuuint32_t*, const cuuint32_t*, CUtensorMapInterleave, CUtensorMapSwizzle,
                             CUtensorMapL2promotion, CUtensorMapFloatOOBfill);

void encode(EncodeFn fn, CUtensorMap* m, const void* p, int rank, const cuuint64_t* dims, const cuuint64_t* strides,
            const cuuint32_t* box, CUtensorMapSwizzle sw = CU_TENSOR_MAP_SWIZZLE_128B) {
  const cuuint32_t es[3] = {1, 1, 1};
  fn(m, CU_TENSOR_MAP_DATA_TYPE_BFLOAT16, rank, const_cast<void*>(p), dims, strides, box, es, CU_TENSOR_MAP_INTERLEAVE_NONE,
     sw, CU_TENSOR_MAP_L2_PROMOTION_L2_128B, CU_TENSOR_MAP_FLOAT_OOB_FILL_NONE);
}
void encode2d(EncodeFn fn, CUtensorMap* m, const void* p, uint64_t cols, uint64_t rows, uint32_t bc, uint32_t br,
              CUtensorMapSwizzle sw = CU_TENSOR_MAP_SWIZZLE_128B) {
  const cuuint64_t dims[2] = {cols, rows}, strides[1] = {cols * 2};
  const cuuint32_t box[2] = {bc, br};
  encode(fn, m, p, 2, dims, strides, box, sw);
}

}

extern "C" void kernel_launch(void* const* d_in, const int* in_sizes, int n_in, void* d_out, int out_size) {
  (void)in_sizes; (void)n_in; (void)out_size;
  void* fp = nullptr;
  cudaDriverEntryPointQueryResult qr;
  cudaGetDriverEntryPoint("cuTensorMapEncodeTiled", &fp, cudaEnableDefault, &qr);
  EncodeFn fn = (EncodeFn)fp;
  Maps maps;
  {
    const cuuint64_t dims[3] = {448, 448, 3}, strides[2] = {1344 * 2, 448 * 2};
    const cuuint32_t box[3] = {64, 32, 3};
    encode(fn, &maps.qkv, d_in[1], 3, dims, strides, box);
  }
  encode2d(fn, &maps.g64, d_in[4], 1792, 448, 64, 64);
  encode2d(fn, &maps.g32, d_in[4], 1792, 448, 32, 64, CU_TENSOR_MAP_SWIZZLE_64B);
  encode2d(fn, &maps.u64, d_in[5], 1792, 448, 64, 64);
  encode2d(fn, &maps.u32, d_in[5], 1792, 448, 32, 64, CU_TENSOR_MAP_SWIZZLE_64B);
  encode2d(fn, &maps.down, d_in[6], 448, 1792, 64, 32);
  encode2d(fn, &maps.down64, d_in[6], 448, 1792, 64, 64);
  encode2d(fn, &maps.wo, d_in[2], 448, 448, 64, 64);
  encode2d(fn, &maps.out, d_out, 448, 2048, 64, 64);
  cudaFuncSetAttribute(fused_kernel, cudaFuncAttributeMaxDynamicSharedMemorySize, SMEM_BYTES);
  fused_kernel<<<128, 512, SMEM_BYTES>>>((const uint8_t*)d_in[0], (const __nv_bfloat16*)d_in[7],
                                         (__nv_bfloat16*)d_out, maps);
}
```

```cpp
#include <cuda_runtime.h>
#include <cuda_bf16.h>
#include <cuda.h>
#include <stdint.h>

namespace {

constexpr int NSLOT = 4;
constexpr int XAHEAD = 2;
constexpr uint32_t SB = 0x400;
constexpr uint32_t OFF_X = SB;
constexpr uint32_t OFF_QO = OFF_X + 114688;
constexpr uint32_t OFF_KV = OFF_QO + 16384;
constexpr uint32_t OFF_E = OFF_QO;
constexpr uint32_t OFF_RING = OFF_KV + 32768;
constexpr uint32_t OFF_BAR = OFF_RING + NSLOT * 16384;
constexpr uint32_t OFF_G = OFF_BAR + 768;
constexpr uint32_t OFF_EPOCH = OFF_G + 512;
constexpr uint32_t OFF_GW = OFF_EPOCH + 128;
constexpr uint32_t SMEM_BYTES = OFF_GW + 896 - SB;

constexpr uint32_t B_EFULL = OFF_BAR;
constexpr uint32_t B_FULL = B_EFULL + 8 * 4;
constexpr uint32_t B_KVFULL = B_FULL + 8 * NSLOT;
constexpr uint32_t B_ZOK = B_KVFULL + 8 * 2;
constexpr uint32_t B_SLOW = B_ZOK + 8;
constexpr uint32_t B_SETTLED = B_SLOW + 8;
constexpr uint32_t B_PUB = B_SETTLED + 8;
constexpr uint32_t B_GW = B_PUB + 8 * 3;
constexpr uint32_t B_GFULL = B_GW + 8 * 15;
constexpr uint32_t B_GO = B_GFULL + 8 * 3;
constexpr uint32_t B_LFULL = B_GO + 8 * 2;
constexpr uint32_t B_SHIPPED = B_LFULL + 8 * 6;
constexpr uint32_t B_EPOCH = B_SHIPPED + 8 * 2;
constexpr uint32_t B_EMPTY = B_EPOCH + 8;
constexpr uint32_t B_EEMPTY = B_EMPTY + 8 * NSLOT;
constexpr uint32_t B_GEMPTY = B_EEMPTY + 8 * 4;
constexpr uint32_t B_VRDY = B_GEMPTY + 8 * 3;
constexpr uint32_t B_GRDY = B_VRDY + 8;
constexpr uint32_t B_RCVD = B_GRDY + 8;
constexpr uint32_t B_XFULL = B_RCVD + 8;
constexpr uint32_t B_KVEMPTY = B_XFULL + 8 * 7;
constexpr uint32_t B_QKRDY = B_KVEMPTY + 8 * 2;
constexpr uint32_t B_ORDY = B_QKRDY + 8 * 2;
constexpr uint32_t B_ZRDY = B_ORDY + 8 * 2;
constexpr uint32_t B_K1RDY = B_ZRDY + 8;
constexpr uint32_t B_ATTDONE = B_K1RDY + 8;
constexpr uint32_t B_OUT = B_ATTDONE + 8;
constexpr uint32_t B_END = B_OUT + 8 * 14;
static_assert(B_KVEMPTY % 16 == 0, "toggled with ^ 8");
static_assert(B_END <= OFF_G, "barriers overflow");

constexpr uint32_t DESC_HI = 0x40000040u;
constexpr uint32_t DESC_HI64 = 0x80000020u;
constexpr uint32_t SPIN_LIMIT = 1u << 18;
constexpr uint32_t POLL_LIMIT = 1u << 23;

constexpr int IT_P1 = 6, IT_P2 = 13, IT_P3 = 20, IT_P4 = 24;
constexpr uint32_t G2_BYTES = 36864;
constexpr int G2A = 3, G2B = 7;
__host__ __device__ constexpr uint32_t g2_buf(uint32_t i) { return i < 2 ? OFF_X + i * G2_BYTES : OFF_RING; }
__host__ __device__ constexpr uint32_t out_tile(uint32_t i) { return i < 5 ? OFF_X + 73728 + i * 8192 : OFF_RING + i * 8192; }

__device__ __forceinline__ int g2_col(int p, int rank) {
  return 64 * (p == 1 ? 6 : ((p & 1) || p == 6 ? 3 - 3 * rank + (p >> 1) - 1 : 3 * rank + (p >> 1)));
}

__device__ __forceinline__ uint32_t g2_tile(int p, int w) {
  return p == 1 ? OFF_QO + w * 8192
                : ((p & 1) || p == 6 ? out_tile(2 * ((p >> 1) - 1) + w) : (p == 0 ? out_tile(6) : OFF_KV + (p - 2) * 8192) + w * 8192);
}

struct alignas(64) Maps {
  CUtensorMap qkv, g64, g32, u64, u32, down, down64, wo, out;
};

struct alignas(128) Exchange {
  uint8_t kv[2][16384];
  unsigned flag, epoch;
};
__device__ Exchange g_ex[128];
__device__ unsigned g_zflag[16 * 8];
__device__ __forceinline__ const uint8_t* kv_block(int kb, int j) { return g_ex[(kb >> 1) * 8 + j].kv[kb & 1]; }

__device__ __forceinline__ uint32_t smem_u32(const void* p) { return (uint32_t)__cvta_generic_to_shared(p); }
extern __shared__ __align__(1024) uint8_t smem_raw[];
__device__ __forceinline__ uint32_t self(uint32_t a) { return a + (smem_u32(smem_raw) - SB); }
__device__ __forceinline__ uint32_t in_cta(uint32_t a, uint32_t rank) {
  uint32_t r;
  asm("mapa.shared::cluster.u32 %0, %1, %2;" : "=r"(r) : "r"(self(a)), "r"(rank));
  return r;
}
__device__ __forceinline__ void mbar_init(uint32_t bar, uint32_t cnt) {
  asm volatile("mbarrier.init.shared::cta.b64 [%0], %1;" ::"r"(self(bar)), "r"(cnt) : "memory");
}
__device__ __forceinline__ void mbar_expect_tx(uint32_t bar, uint32_t bytes) {
  asm volatile("mbarrier.arrive.expect_tx.shared::cta.b64 _, [%0], %1;" ::"r"(self(bar)), "r"(bytes) : "memory");
}
__device__ __forceinline__ void mbar_arrive(uint32_t bar) {
  asm volatile("mbarrier.arrive.shared::cta.b64 _, [%0];" ::"r"(self(bar)) : "memory");
}
__device__ __forceinline__ void mbar_arrive_if(bool pred, uint32_t bar) {
  asm volatile("{\n.reg .pred p;\nsetp.ne.u32 p, %1, 0;\n@p mbarrier.arrive.shared::cta.b64 _, [%0];\n}" ::"r"(self(bar)), "r"((uint32_t)pred) : "memory");
}
__device__ __forceinline__ void mbar_wait(uint32_t bar, uint32_t parity) {
  asm volatile(
      "{\n.reg .pred p;\n.reg .u32 n;\n"
      "mbarrier.try_wait.parity.shared::cta.b64 p, [%0], %1;\n"
      "@p bra DONE;\n"
      "mov.u32 n, 0;\n"
      "LOOP:\n"
      "mbarrier.try_wait.parity.shared::cta.b64 p, [%0], %1, 20000;\n"
      "@p bra DONE;\n"
      "add.u32 n, n, 1;\n"
      "setp.lt.u32 p, n, %2;\n"
      "@p bra LOOP;\n"
      "trap;\n"
      "DONE:\n}" ::"r"(self(bar)), "r"(parity), "n"(SPIN_LIMIT) : "memory");
}
__device__ __forceinline__ uint32_t mbar_try(uint32_t bar, uint32_t parity) {
  uint32_t ok;
  asm volatile("{\n.reg .pred p;\nmbarrier.test_wait.parity.shared::cta.b64 p, [%1], %2;\nselp.u32 %0, 1, 0, p;\n}"
               : "=r"(ok) : "r"(self(bar)), "r"(parity) : "memory");
  return ok;
}
__device__ __forceinline__ bool elect_one() {
  uint32_t ok;
  asm volatile("{\n.reg .pred p;\nelect.sync _|p, 0xffffffff;\nselp.u32 %0, 1, 0, p;\n}" : "=r"(ok));
  return ok != 0;
}
__device__ __forceinline__ void bulk_load(uint32_t dst, const void* src, uint32_t bytes, uint32_t bar) {
  asm volatile("cp.async.bulk.shared::cluster.global.mbarrier::complete_tx::bytes [%0], [%1], %2, [%3];"
               ::"r"(self(dst)), "l"(src), "r"(bytes), "r"(self(bar)) : "memory");
}
__device__ __forceinline__ unsigned flag_wait(const unsigned* p, unsigned want) {
  unsigned v, n = 0;
  while (true) {
    asm volatile("ld.acquire.gpu.global.u32 %0, [%1];" : "=r"(v) : "l"(p) : "memory");
    if ((int)(v - want) >= 0) break;
    if (++n > POLL_LIMIT) __trap();
  }
  return v;
}
__device__ __forceinline__ void tma2d(uint32_t dst, const CUtensorMap* m, int c0, int c1, uint32_t bar) {
  asm volatile("cp.async.bulk.tensor.2d.shared::cluster.global.mbarrier::complete_tx::bytes [%0], [%1, {%3, %4}], [%2];"
               ::"r"(self(dst)), "l"(m), "r"(self(bar)), "r"(c0), "r"(c1) : "memory");
}
__device__ __forceinline__ void tma3d(uint32_t dst, const CUtensorMap* m, int c0, int c1, int c2, uint32_t bar) {
  asm volatile("cp.async.bulk.tensor.3d.shared::cluster.global.mbarrier::complete_tx::bytes [%0], [%1, {%3, %4, %5}], [%2];"
               ::"r"(self(dst)), "l"(m), "r"(self(bar)), "r"(c0), "r"(c1), "r"(c2) : "memory");
}
__device__ __forceinline__ void wg_fence() { asm volatile("wgmma.fence.sync.aligned;" ::: "memory"); }
__device__ __forceinline__ void wg_commit() { asm volatile("wgmma.commit_group.sync.aligned;" ::: "memory"); }
template <int N> __device__ __forceinline__ void wg_wait() { asm volatile("wgmma.wait_group.sync.aligned %0;" ::"n"(N) : "memory"); }
template <int N> __device__ __forceinline__ void reg_fence(float (&d)[N]) {
#pragma unroll
  for (int i = 0; i < N; i++) asm volatile("" : "+f"(d[i])::"memory");
}
template <int N> __device__ __forceinline__ void reg_fence(uint32_t (&d)[N]) {
#pragma unroll
  for (int i = 0; i < N; i++) asm volatile("" : "+r"(d[i])::"memory");
}
__device__ __forceinline__ void fence_async_smem() { asm volatile("fence.proxy.async.shared::cta;" ::: "memory"); }
__device__ __forceinline__ void fence_async_global() { asm volatile("fence.proxy.async.global;" ::: "memory"); }
__device__ __forceinline__ uint32_t pack_bf16(float lo, float hi) {
  uint32_t r;
  asm("cvt.rn.bf16x2.f32 %0, %1, %2;" : "=r"(r) : "f"(hi), "f"(lo));
  return r;
}
__device__ __forceinline__ void sts32(uint32_t a, uint32_t v) { asm volatile("st.shared.u32 [%0], %1;" ::"r"(self(a)), "r"(v) : "memory"); }
__device__ __forceinline__ void sts128(uint32_t a, uint32_t r0, uint32_t r1, uint32_t r2, uint32_t r3) {
  asm volatile("st.shared.v4.u32 [%0], {%1, %2, %3, %4};" ::"r"(self(a)), "r"(r0), "r"(r1), "r"(r2), "r"(r3) : "memory");
}
__device__ __forceinline__ uint32_t add_bf16x2(uint32_t a, uint32_t b) {
  uint32_t r;
  asm("add.rn.bf16x2 %0, %1, %2;" : "=r"(r) : "r"(a), "r"(b));
  return r;
}
__device__ __forceinline__ void stsm4(uint32_t a, uint32_t r0, uint32_t r1, uint32_t r2, uint32_t r3) {
  asm volatile("stmatrix.sync.aligned.m8n8.x4.shared.b16 [%0], {%1, %2, %3, %4};" ::"r"(self(a)), "r"(r0), "r"(r1), "r"(r2), "r"(r3) : "memory");
}
__device__ __forceinline__ float lds_f32(uint32_t a) {
  float v;
  asm volatile("ld.shared.f32 %0, [%1];" : "=f"(v) : "r"(self(a)) : "memory");
  return v;
}
__device__ __forceinline__ uint4 lds128(uint32_t a) {
  uint4 v;
  asm volatile("ld.shared.v4.u32 {%0, %1, %2, %3}, [%4];" : "=r"(v.x), "=r"(v.y), "=r"(v.z), "=r"(v.w) : "r"(self(a)) : "memory");
  return v;
}
__device__ __forceinline__ float ex2(float x) {
  float y;
  asm("ex2.approx.ftz.f32 %0, %1;" : "=f"(y) : "f"(x));
  return y;
}
__device__ __forceinline__ float tanh_fast(float x) {
  float y;
  asm("tanh.approx.f32 %0, %1;" : "=f"(y) : "f"(x));
  return y;
}
__host__ __device__ constexpr uint32_t desc_lo(uint32_t addr, uint32_t lbo) { return ((addr & 0x3FFFFu) >> 4) | ((lbo >> 4) << 16); }
__device__ __forceinline__ void sched_fence() {
  asm volatile("pmevent 0;" ::: "memory");
}

__device__ __forceinline__ void mma_qkv(float (&d)[92], uint32_t alo, uint32_t blo, uint32_t bhi, int scale_d) {
  asm volatile("{\n.reg .pred p;\n.reg .b64 da, db;\nsetp.ne.b32 p, %95, 0;\nmov.b64 da, {%92, %96};\nmov.b64 db, {%93, %94};\n"
    "wgmma.mma_async.sync.aligned.m64n184k16.f32.bf16.bf16 {"
    "%0, %1, %2, %3, %4, %5, %6, %7, %8, %9, %10, %11, %12, %13, %14, %15, "
    "%16, %17, %18, %19, %20, %21, %22, %23, %24, %25, %26, %27, %28, %29, %30, %31, "
    "%32, %33, %34, %35, %36, %37, %38, %39, %40, %41, %42, %43, %44, %45, %46, %47, "
    "%48, %49, %50, %51, %52, %53, %54, %55, %56, %57, %58, %59, %60, %61, %62, %63, "
    "%64, %65, %66, %67, %68, %69, %70, %71, %72, %73, %74, %75, %76, %77, %78, %79, "
    "%80, %81, %82, %83, %84, %85, %86, %87, %88, %89, %90, %91"
    "}, da, db, p, 1, 1, 0, 1;\n}\n"
    : "+f"(d[0]), "+f"(d[1]), "+f"(d[2]), "+f"(d[3]), "+f"(d[4]), "+f"(d[5]), "+f"(d[6]), "+f"(d[7]),
      "+f"(d[8]), "+f"(d[9]), "+f"(d[10]), "+f"(d[11]), "+f"(d[12]), "+f"(d[13]), "+f"(d[14]), "+f"(d[15]),
      "+f"(d[16]), "+f"(d[17]), "+f"(d[18]), "+f"(d[19]), "+f"(d[20]), "+f"(d[21]), "+f"(d[22]), "+f"(d[23]),
      "+f"(d[24]), "+f"(d[25]), "+f"(d[26]), "+f"(d[27]), "+f"(d[28]), "+f"(d[29]), "+f"(d[30]), "+f"(d[31]),
      "+f"(d[32]), "+f"(d[33]), "+f"(d[34]), "+f"(d[35]), "+f"(d[36]), "+f"(d[37]), "+f"(d[38]), "+f"(d[39]),
      "+f"(d[40]), "+f"(d[41]), "+f"(d[42]), "+f"(d[43]), "+f"(d[44]), "+f"(d[45]), "+f"(d[46]), "+f"(d[47]),
      "+f"(d[48]), "+f"(d[49]), "+f"(d[50]), "+f"(d[51]), "+f"(d[52]), "+f"(d[53]), "+f"(d[54]), "+f"(d[55]),
      "+f"(d[56]), "+f"(d[57]), "+f"(d[58]), "+f"(d[59]), "+f"(d[60]), "+f"(d[61]), "+f"(d[62]), "+f"(d[63]),
      "+f"(d[64]), "+f"(d[65]), "+f"(d[66]), "+f"(d[67]), "+f"(d[68]), "+f"(d[69]), "+f"(d[70]), "+f"(d[71]),
      "+f"(d[72]), "+f"(d[73]), "+f"(d[74]), "+f"(d[75]), "+f"(d[76]), "+f"(d[77]), "+f"(d[78]), "+f"(d[79]),
      "+f"(d[80]), "+f"(d[81]), "+f"(d[82]), "+f"(d[83]), "+f"(d[84]), "+f"(d[85]), "+f"(d[86]), "+f"(d[87]),
      "+f"(d[88]), "+f"(d[89]), "+f"(d[90]), "+f"(d[91])
    : "r"(alo), "r"(blo), "r"(bhi), "r"(scale_d), "r"(DESC_HI));
}
__device__ __forceinline__ void mma_n128(float (&d)[64], uint32_t alo, uint32_t blo, uint32_t bhi, int scale_d) {
  asm volatile("{\n.reg .pred p;\n.reg .b64 da, db;\nsetp.ne.b32 p, %67, 0;\nmov.b64 da, {%64, %68};\nmov.b64 db, {%65, %66};\n"
    "wgmma.mma_async.sync.aligned.m64n128k16.f32.bf16.bf16 {"
    "%0, %1, %2, %3, %4, %5, %6, %7, %8, %9, %10, %11, %12, %13, %14, %15, "
    "%16, %17, %18, %19, %20, %21, %22, %23, %24, %25, %26, %27, %28, %29, %30, %31, "
    "%32, %33, %34, %35, %36, %37, %38, %39, %40, %41, %42, %43, %44, %45, %46, %47, "
    "%48, %49, %50, %51, %52, %53, %54, %55, %56, %57, %58, %59, %60, %61, %62, %63"
    "}, da, db, p, 1, 1, 0, 1;\n}\n"
    : "+f"(d[0]), "+f"(d[1]), "+f"(d[2]), "+f"(d[3]), "+f"(d[4]), "+f"(d[5]), "+f"(d[6]), "+f"(d[7]),
      "+f"(d[8]), "+f"(d[9]), "+f"(d[10]), "+f"(d[11]), "+f"(d[12]), "+f"(d[13]), "+f"(d[14]), "+f"(d[15]),
      "+f"(d[16]), "+f"(d[17]), "+f"(d[18]), "+f"(d[19]), "+f"(d[20]), "+f"(d[21]), "+f"(d[22]), "+f"(d[23]),
      "+f"(d[24]), "+f"(d[25]), "+f"(d[26]), "+f"(d[27]), "+f"(d[28]), "+f"(d[29]), "+f"(d[30]), "+f"(d[31]),
      "+f"(d[32]), "+f"(d[33]), "+f"(d[34]), "+f"(d[35]), "+f"(d[36]), "+f"(d[37]), "+f"(d[38]), "+f"(d[39]),
      "+f"(d[40]), "+f"(d[41]), "+f"(d[42]), "+f"(d[43]), "+f"(d[44]), "+f"(d[45]), "+f"(d[46]), "+f"(d[47]),
      "+f"(d[48]), "+f"(d[49]), "+f"(d[50]), "+f"(d[51]), "+f"(d[52]), "+f"(d[53]), "+f"(d[54]), "+f"(d[55]),
      "+f"(d[56]), "+f"(d[57]), "+f"(d[58]), "+f"(d[59]), "+f"(d[60]), "+f"(d[61]), "+f"(d[62]), "+f"(d[63])
    : "r"(alo), "r"(blo), "r"(bhi), "r"(scale_d), "r"(DESC_HI));
}
__device__ __forceinline__ void mma_rs64(float (&d)[32], uint32_t a0, uint32_t a1, uint32_t a2, uint32_t a3, uint32_t blo, uint32_t bhi, int scale_d) {
  asm volatile("{\n.reg .pred p;\n.reg .b64 db;\nsetp.ne.b32 p, %38, 0;\nmov.b64 db, {%36, %37};\n"
    "wgmma.mma_async.sync.aligned.m64n64k16.f32.bf16.bf16 {"
    "%0, %1, %2, %3, %4, %5, %6, %7, %8, %9, %10, %11, %12, %13, %14, %15, "
    "%16, %17, %18, %19, %20, %21, %22, %23, %24, %25, %26, %27, %28, %29, %30, %31"
    "}, {%32, %33, %34, %35}, db, p, 1, 1, 1;\n}\n"
    : "+f"(d[0]), "+f"(d[1]), "+f"(d[2]), "+f"(d[3]), "+f"(d[4]), "+f"(d[5]), "+f"(d[6]), "+f"(d[7]),
      "+f"(d[8]), "+f"(d[9]), "+f"(d[10]), "+f"(d[11]), "+f"(d[12]), "+f"(d[13]), "+f"(d[14]), "+f"(d[15]),
      "+f"(d[16]), "+f"(d[17]), "+f"(d[18]), "+f"(d[19]), "+f"(d[20]), "+f"(d[21]), "+f"(d[22]), "+f"(d[23]),
      "+f"(d[24]), "+f"(d[25]), "+f"(d[26]), "+f"(d[27]), "+f"(d[28]), "+f"(d[29]), "+f"(d[30]), "+f"(d[31])
    : "r"(a0), "r"(a1), "r"(a2), "r"(a3), "r"(blo), "r"(bhi), "r"(scale_d));
}
__device__ __forceinline__ void mma_ss64(float (&d)[32], uint32_t alo, uint32_t blo, uint32_t bhi, int scale_d) {
  asm volatile("{\n.reg .pred p;\n.reg .b64 da, db;\nsetp.ne.b32 p, %35, 0;\nmov.b64 da, {%32, %36};\nmov.b64 db, {%33, %34};\n"
    "wgmma.mma_async.sync.aligned.m64n64k16.f32.bf16.bf16 {"
    "%0, %1, %2, %3, %4, %5, %6, %7, %8, %9, %10, %11, %12, %13, %14, %15, "
    "%16, %17, %18, %19, %20, %21, %22, %23, %24, %25, %26, %27, %28, %29, %30, %31"
    "}, da, db, p, 1, 1, 0, 1;\n}\n"
    : "+f"(d[0]), "+f"(d[1]), "+f"(d[2]), "+f"(d[3]), "+f"(d[4]), "+f"(d[5]), "+f"(d[6]), "+f"(d[7]),
      "+f"(d[8]), "+f"(d[9]), "+f"(d[10]), "+f"(d[11]), "+f"(d[12]), "+f"(d[13]), "+f"(d[14]), "+f"(d[15]),
      "+f"(d[16]), "+f"(d[17]), "+f"(d[18]), "+f"(d[19]), "+f"(d[20]), "+f"(d[21]), "+f"(d[22]), "+f"(d[23]),
      "+f"(d[24]), "+f"(d[25]), "+f"(d[26]), "+f"(d[27]), "+f"(d[28]), "+f"(d[29]), "+f"(d[30]), "+f"(d[31])
    : "r"(alo), "r"(blo), "r"(bhi), "r"(scale_d), "r"(DESC_HI));
}
__device__ __forceinline__ void mma_s(float (&d)[32], uint32_t alo, uint32_t blo, uint32_t bhi, int scale_d) {
  asm volatile("{\n.reg .pred p;\n.reg .b64 da, db;\nsetp.ne.b32 p, %35, 0;\nmov.b64 da, {%32, %36};\nmov.b64 db, {%33, %34};\n"
    "wgmma.mma_async.sync.aligned.m64n64k16.f32.bf16.bf16 {"
    "%0, %1, %2, %3, %4, %5, %6, %7, %8, %9, %10, %11, %12, %13, %14, %15, "
    "%16, %17, %18, %19, %20, %21, %22, %23, %24, %25, %26, %27, %28, %29, %30, %31"
    "}, da, db, p, 1, 1, 0, 0;\n}\n"
    : "+f"(d[0]), "+f"(d[1]), "+f"(d[2]), "+f"(d[3]), "+f"(d[4]), "+f"(d[5]), "+f"(d[6]), "+f"(d[7]),
      "+f"(d[8]), "+f"(d[9]), "+f"(d[10]), "+f"(d[11]), "+f"(d[12]), "+f"(d[13]), "+f"(d[14]), "+f"(d[15]),
      "+f"(d[16]), "+f"(d[17]), "+f"(d[18]), "+f"(d[19]), "+f"(d[20]), "+f"(d[21]), "+f"(d[22]), "+f"(d[23]),
      "+f"(d[24]), "+f"(d[25]), "+f"(d[26]), "+f"(d[27]), "+f"(d[28]), "+f"(d[29]), "+f"(d[30]), "+f"(d[31])
    : "r"(alo), "r"(blo), "r"(bhi), "r"(scale_d), "r"(DESC_HI));
}
__device__ __forceinline__ void mma_s0(float (&d)[32], uint32_t alo, uint32_t blo, uint32_t bhi) {
  asm volatile("{\n.reg .pred p;\n.reg .b64 da, db;\nsetp.ne.b32 p, %35, 0;\nmov.b64 da, {%32, %36};\nmov.b64 db, {%33, %34};\n"
    "wgmma.mma_async.sync.aligned.m64n64k16.f32.bf16.bf16 {"
    "%0, %1, %2, %3, %4, %5, %6, %7, %8, %9, %10, %11, %12, %13, %14, %15, "
    "%16, %17, %18, %19, %20, %21, %22, %23, %24, %25, %26, %27, %28, %29, %30, %31"
    "}, da, db, p, 1, 1, 0, 0;\n}\n"
    : "=f"(d[0]), "=f"(d[1]), "=f"(d[2]), "=f"(d[3]), "=f"(d[4]), "=f"(d[5]), "=f"(d[6]), "=f"(d[7]),
      "=f"(d[8]), "=f"(d[9]), "=f"(d[10]), "=f"(d[11]), "=f"(d[12]), "=f"(d[13]), "=f"(d[14]), "=f"(d[15]),
      "=f"(d[16]), "=f"(d[17]), "=f"(d[18]), "=f"(d[19]), "=f"(d[20]), "=f"(d[21]), "=f"(d[22]), "=f"(d[23]),
      "=f"(d[24]), "=f"(d[25]), "=f"(d[26]), "=f"(d[27]), "=f"(d[28]), "=f"(d[29]), "=f"(d[30]), "=f"(d[31])
    : "r"(alo), "r"(blo), "r"(bhi), "n"(0), "r"(DESC_HI));
}
__device__ __forceinline__ void mma_pv(float (&d)[16], uint32_t a0, uint32_t a1, uint32_t a2, uint32_t a3, uint32_t blo, uint32_t bhi, int scale_d) {
  asm volatile("{\n.reg .pred p;\n.reg .b64 db;\nsetp.ne.b32 p, %22, 0;\nmov.b64 db, {%20, %21};\n"
    "wgmma.mma_async.sync.aligned.m64n32k16.f32.bf16.bf16 {"
    "%0, %1, %2, %3, %4, %5, %6, %7, %8, %9, %10, %11, %12, %13, %14, %15"
    "}, {%16, %17, %18, %19}, db, p, 1, 1, 1;\n}\n"
    : "+f"(d[0]), "+f"(d[1]), "+f"(d[2]), "+f"(d[3]), "+f"(d[4]), "+f"(d[5]), "+f"(d[6]), "+f"(d[7]),
      "+f"(d[8]), "+f"(d[9]), "+f"(d[10]), "+f"(d[11]), "+f"(d[12]), "+f"(d[13]), "+f"(d[14]), "+f"(d[15])
    : "r"(a0), "r"(a1), "r"(a2), "r"(a3), "r"(blo), "r"(bhi), "r"(scale_d));
}

__device__ __forceinline__ void store_heads(uint32_t rowaddr, uint32_t lane, const uint32_t (&v)[14], uint32_t pad) {
  const uint32_t q = lane & 3;
  uint32_t o[16];
#pragma unroll
  for (int c = 0; c < 8; c++)
#pragma unroll
    for (int hf = 0; hf < 2; hf++) {
      uint32_t x = c < 7 ? v[2 * c + hf] : pad;
      if ((c & 1) && c < 7) x = q == (7u - c) / 2 ? pad : x;
      if (c >= 2) x = q >= 4u - c / 2 ? v[2 * (c - 1) + hf] : x;
      o[2 * c + hf] = x;
    }
#pragma unroll
  for (int g = 0; g < 4; g++)
    stsm4(rowaddr + (((2 * g + (lane >> 4)) ^ (lane & 7)) << 4), o[4 * g], o[4 * g + 1], o[4 * g + 2], o[4 * g + 3]);
}

constexpr float SM_C = 0.18898223650461361f * 1.4426950408889634f;

struct RowStat {
  float m0, m1;
  float al0, al1;
};

__device__ __forceinline__ void mask_block(float (&s)[32], bool diag, int row0, int row1, int q) {
  const float NEG = __int_as_float(0xff800000);
  const int t0 = row0 - 2 * q, t1 = row1 - 2 * q;
#pragma unroll
  for (int g = 0; g < 8; g++) {
    if (((8 * g) <= t0) != diag) s[4 * g] = NEG;
    if (((8 * g + 1) <= t0) != diag) s[4 * g + 1] = NEG;
    if (((8 * g) <= t1) != diag) s[4 * g + 2] = NEG;
    if (((8 * g + 1) <= t1) != diag) s[4 * g + 3] = NEG;
  }
}

__device__ __forceinline__ void update_max(const float (&s)[32], RowStat& r, bool first) {
  const float p0 = first ? __int_as_float(0xff800000) : r.m0, p1 = first ? __int_as_float(0xff800000) : r.m1;
  float a0 = fmaxf(s[0], s[1]), a1 = fmaxf(s[2], s[3]), b0 = fmaxf(s[4], s[5]), b1 = fmaxf(s[6], s[7]);
#pragma unroll
  for (int g = 2; g < 8; g += 2) {
    a0 = fmaxf(a0, fmaxf(s[4 * g], s[4 * g + 1]));
    a1 = fmaxf(a1, fmaxf(s[4 * g + 2], s[4 * g + 3]));
    b0 = fmaxf(b0, fmaxf(s[4 * g + 4], s[4 * g + 5]));
    b1 = fmaxf(b1, fmaxf(s[4 * g + 6], s[4 * g + 7]));
  }
  a0 = fmaxf(fmaxf(a0, b0), p0);
  a1 = fmaxf(fmaxf(a1, b1), p1);
  a0 = fmaxf(a0, __shfl_xor_sync(~0u, a0, 1));
  a1 = fmaxf(a1, __shfl_xor_sync(~0u, a1, 1));
  a0 = fmaxf(a0, __shfl_xor_sync(~0u, a0, 2));
  a1 = fmaxf(a1, __shfl_xor_sync(~0u, a1, 2));
  r.al0 = ex2(p0 - a0);
  r.al1 = ex2(p1 - a1);
  r.m0 = a0;
  r.m1 = a1;
}

__device__ __forceinline__ void exp_shifted(float (&s)[32], float m0, float m1) {
#pragma unroll
  for (int g = 0; g < 8; g++) {
    s[4 * g] = ex2(s[4 * g] - m0);
    s[4 * g + 1] = ex2(s[4 * g + 1] - m0);
    s[4 * g + 2] = ex2(s[4 * g + 2] - m1);
    s[4 * g + 3] = ex2(s[4 * g + 3] - m1);
  }
}
template <int TYPE> __host__ __device__ constexpr bool pair_dead(int i) {
  return TYPE == 1 ? (i >= 8 && !(i & 1)) : (TYPE == 2 ? (i < 8 && (i & 1)) : false);
}
template <int TYPE, int I0, int I1> __device__ __forceinline__ void ex2_pairs(float (&s)[32]) {
#pragma unroll
  for (int i = 2 * I0; i < 2 * I1; i++)
    if (!pair_dead<TYPE>(i >> 1)) asm("ex2.approx.ftz.f32 %0, %0;" : "+f"(s[i]));
}

__device__ __forceinline__ void issue_s(float (&s)[32], uint32_t qlo, uint32_t klo) {
  wg_fence();
  mma_s0(s, qlo, klo, DESC_HI);
  mma_s(s, qlo + 2, klo + 2, DESC_HI, 1);
  wg_commit();
  sched_fence();
}
__device__ __forceinline__ void issue_pv(float (&o)[16], const uint32_t (&p)[16], uint32_t vlo, int acc_o) {
  wg_fence();
  mma_pv(o, p[0], p[1], p[2], p[3], vlo, DESC_HI, acc_o);
  mma_pv(o, p[4], p[5], p[6], p[7], vlo + 128, DESC_HI, 1);
  mma_pv(o, p[8], p[9], p[10], p[11], vlo + 256, DESC_HI, 1);
  mma_pv(o, p[12], p[13], p[14], p[15], vlo + 384, DESC_HI, 1);
  wg_commit();
  sched_fence();
}
__device__ __forceinline__ void issue_s_pv(float (&s)[32], uint32_t qlo, uint32_t klo, float (&o)[16], const uint32_t (&p)[16],
                                           uint32_t vlo, int acc_o) {
  wg_fence();
  mma_pv(o, p[0], p[1], p[2], p[3], vlo, DESC_HI, acc_o);
  mma_pv(o, p[4], p[5], p[6], p[7], vlo + 128, DESC_HI, 1);
  mma_pv(o, p[8], p[9], p[10], p[11], vlo + 256, DESC_HI, 1);
  mma_pv(o, p[12], p[13], p[14], p[15], vlo + 384, DESC_HI, 1);
  mma_s0(s, qlo, klo, DESC_HI);
  mma_s(s, qlo + 2, klo + 2, DESC_HI, 1);
  wg_commit();
  sched_fence();
}
__device__ __forceinline__ float rcp_fast(float x) {
  float y;
  asm("rcp.approx.ftz.f32 %0, %1;" : "=f"(y) : "f"(x));
  return y;
}
__device__ __forceinline__ void pack_p(const float (&s)[32], uint32_t (&p)[16]) {
#pragma unroll
  for (int i = 0; i < 16; i++) p[i] = pack_bf16(s[2 * i], s[2 * i + 1]);
}
struct PMask { uint32_t d[4], flip[4]; };
template <int TYPE> __device__ __forceinline__ void pack_masked(const float (&s)[32], uint32_t (&p)[16], const PMask& mk) {
#pragma unroll
  for (int i = 0; i < 16; i++) {
    uint32_t v = 0u;
    if (!pair_dead<TYPE>(i)) v = pack_bf16(s[2 * i], s[2 * i + 1]);
    if (TYPE != 0 && i < 8 && !(i & 1)) v = TYPE == 1 ? v & mk.d[i >> 1] : v & ~mk.d[i >> 1];
    if (TYPE != 0 && i >= 8 && (i & 1)) {
      const int k = 7 - (i >> 1);
      if (TYPE == 1) asm("lop3.b32 %0, %0, %1, %2, 0x60;" : "+r"(v) : "r"(mk.d[k]), "r"(mk.flip[k]));
      else asm("lop3.b32 %0, %0, %1, %2, 0x90;" : "+r"(v) : "r"(mk.d[k]), "r"(mk.flip[k]));
    }
    asm volatile("mov.b32 %0, %1;" : "=r"(p[i]) : "r"(v));
  }
}

template <int NG, int N>
__device__ __forceinline__ void glu_group(uint32_t* h, const float (&acc)[N], int g, float a0, float a1) {
  const float* gt = acc + 4 * g;
  const float* up = acc + 4 * (NG + g);
  const float u0 = a0 * up[0], u1 = a0 * up[1], u2 = a1 * up[2], u3 = a1 * up[3];
  h[2 * g] = pack_bf16(fmaf(u0, tanh_fast(0.5f * gt[0]), u0), fmaf(u1, tanh_fast(0.5f * gt[1]), u1));
  h[2 * g + 1] = pack_bf16(fmaf(u2, tanh_fast(0.5f * gt[2]), u2), fmaf(u3, tanh_fast(0.5f * gt[3]), u3));
  asm volatile("" : "+r"(h[2 * g]), "+r"(h[2 * g + 1])::"memory");
}

template <int IT0, int HS0, class Side>
__device__ __forceinline__ void pass64(float (&acc)[64], uint32_t xlo, bool lane0, Side side) {
#pragma unroll
  for (int hs = HS0; hs < 14; hs++) {
    const int st = hs >> 1, k = (hs & 1) * 2;
    const int slot = (IT0 + st) % NSLOT, ph = ((IT0 + st) / NSLOT) & 1;
    const uint32_t a = xlo + st * 1024 + 2 * k, b = desc_lo(OFF_RING + slot * 16384, 8192) + 128 * k;
    if (!(hs & 1) && (hs > 0 || IT0 != IT_P1)) mbar_wait(B_FULL + 8 * slot, ph);
    wg_fence();
    mma_n128(acc, a, b, DESC_HI, hs != 0);
    mma_n128(acc, a + 2, b + 128, DESC_HI, 1);
    wg_commit();
    sched_fence();
    side(hs);
    sched_fence();
    wg_wait<0>();
    if (hs & 1) mbar_arrive_if(lane0, B_EMPTY + 8 * slot);
  }
  reg_fence(acc);
}

template <int IT0, class Side>
__device__ __forceinline__ void pass32(float (&acc)[32], uint32_t xlo, bool lane0, Side side) {
#pragma unroll
  for (int hs = 0; hs < 7; hs++) {
    const int st = hs >> 1;
    const int slot = (IT0 + st) % NSLOT, ph = ((IT0 + st) / NSLOT) & 1;
    const uint32_t a = xlo + hs * 1024, b = desc_lo(OFF_RING + slot * 16384, 4096) + (hs & 1) * 512;
    if (!(hs & 1)) mbar_wait(B_FULL + 8 * slot, ph);
    wg_fence();
#pragma unroll
    for (int k = 0; k < 4; k++) mma_ss64(acc, a + 2 * k, b + 64 * k, DESC_HI64, (hs | k) != 0);
    wg_commit();
    sched_fence();
    side(hs);
    sched_fence();
    wg_wait<0>();
    if ((hs & 1) || hs == 6) mbar_arrive_if(lane0, B_EMPTY + 8 * slot);
  }
  reg_fence(acc);
}

template <int V> struct Int { static constexpr int value = V; };

struct Ring {
  uint32_t slot, phase;
  __device__ __forceinline__ void next() {
    if (++slot == NSLOT) { slot = 0; phase ^= 1; }
  }
};

__global__ void __cluster_dims__(2, 1, 1) __launch_bounds__(512, 1)
fused_kernel(const uint8_t* __restrict__ x, const uint8_t* __restrict__ wqkv, const __nv_bfloat16* __restrict__ gate_w,
             __nv_bfloat16* __restrict__ out, const __grid_constant__ Maps maps) {
  if (threadIdx.x < 21) asm volatile("prefetch.global.L2 [%0];" ::"l"(wqkv + (blockIdx.x + threadIdx.x * 128) * 128));
  const int warp = __shfl_sync(~0u, (int)(threadIdx.x >> 5), 0);
  const int wg = warp >> 2;
  const int lane = threadIdx.x & 31;
  const int cl = blockIdx.x >> 1, rank = blockIdx.x & 1;
  const int pos = cl < 36 ? (cl - 4) & 7 : (cl - 36) % 7;
  const int blk = cl < 4 ? 0 : (cl < 36 ? (pos < 2 ? 1 - pos : pos) : pos + 1);
  const int k8 = cl < 4 ? cl : (cl < 36 ? ((cl - 4) >> 3) + (blk == 0 ? 4 : 0) : 4 + (cl - 36) / 7);
  const int cta = (((blk >> 1) * 4 + (k8 >> 1)) * 8 + (blk & 1) * 4 + (k8 & 1) * 2 + rank) & 127, m = cta >> 3, j = cta & 7;
  const int wcol = 56 * j - 8 * (j & 1);

  if (wg == 2) {
    const uint32_t t = threadIdx.x & 127, r0 = t >> 3, ch = t & 7;
    const uint8_t* src = x + (size_t)(m * 128 + r0) * 896 + ch * 16;
    const uint32_t dst = OFF_X + r0 * 128 + ((ch ^ (r0 & 7)) << 4);
#pragma unroll
    for (int c = 0; c < 2; c++) {
#pragma unroll
      for (int i = 0; i < 8; i++)
        asm volatile("cp.async.cg.shared.global [%0], [%1], 16;" ::"r"(self(dst + c * 16384 + i * 2048)), "l"(src + c * 128 + i * 16 * 896) : "memory");
      asm volatile("cp.async.commit_group;" ::: "memory");
    }
  } else if (warp == 12) {
    if (elect_one()) {
#pragma unroll
      for (int i = 0; i < 4; i++) mbar_init(B_EFULL + 8 * i, 1);
#pragma unroll
      for (int s = 0; s < 4; s++) {
        mbar_expect_tx(B_EFULL + 8 * s, 12288);
        tma3d(OFF_E + s * 12288, &maps.qkv, wcol, 32 * s, 0, B_EFULL + 8 * s);
      }
    }
  } else if (warp == 13) {
    if (elect_one()) {
      if ((smem_u32(smem_raw) & 0xFFFFFFu) != SB) __trap();
#pragma unroll
      for (uint32_t b = B_FULL; b < B_EMPTY; b += 8) mbar_init(b, 1);
#pragma unroll
      for (int c = 0; c < 6; c++) mbar_expect_tx(B_LFULL + 8 * c, 8192);
    }
  } else if (warp == 15) {
    if (elect_one()) {
#pragma unroll
      for (uint32_t b = B_EMPTY; b < B_END; b += 8)
        mbar_init(b, b < B_XFULL ? 8 : 4);
    }
  } else if (warp == 14) {
    const uint8_t* gw = reinterpret_cast<const uint8_t*>(gate_w) + lane * 16;
    asm volatile("cp.async.cg.shared.global [%0], [%1], 16;" ::"r"(self(OFF_GW + lane * 16)), "l"(gw) : "memory");
    if (lane < 24) asm volatile("cp.async.cg.shared.global [%0], [%1], 16;" ::"r"(self(OFF_GW + 512 + lane * 16)), "l"(gw + 512) : "memory");
    asm volatile("cp.async.commit_group;" ::: "memory");
  }
  __syncthreads();

  if (wg == 3) {
    auto patch_gate = [&](int s0, int s1) {
      const uint32_t prow = lane + (j & 1), poff = prow * 128 + ((((j & 1) ? 0 : 7) ^ (prow & 7)) << 4);
#pragma unroll 1
      for (int s = s0; s < s1; s++) {
        unsigned short v;
        asm volatile("ld.shared.u16 %0, [%1];" : "=h"(v) : "r"(self(OFF_GW + s * 64 + lane * 2)) : "memory");
        for (uint32_t it = 0; !mbar_try(((s & 4) ? B_FULL : B_EFULL) + 8 * (s & 3), s >> 3); it++)
          if (it > (POLL_LIMIT << 4)) __trap();
        const uint32_t buf = (s & 4) ? OFF_RING + (s & 3) * 16384 : OFF_E + (s & 3) * 12288;
        asm volatile("st.shared.u16 [%0], %1;" ::"r"(self(buf + poff)), "h"(v) : "memory");
        __syncwarp();
        mbar_arrive_if(lane == 0, B_GW + 8 * s);
      }
    };
    if (warp == 12) {
      if (elect_one()) {
#pragma unroll 1
        for (int s = 4; s < 8; s++) {
          mbar_expect_tx(B_FULL + 8 * (s - 4), 12288);
          tma3d(OFF_RING + (s - 4) * 16384, &maps.qkv, wcol, 32 * s, 0, B_FULL + 8 * (s - 4));
        }
      }
    } else if (warp == 14) {
      asm volatile("cp.async.wait_group 0;" ::: "memory");
      __syncwarp();
      patch_gate(0, 2);
    }
    __syncwarp();
    asm volatile("setmaxnreg.dec.sync.aligned.u32 24;");
    auto ship = [&](int w) {
      const uint32_t peer = in_cta(SB, rank ^ 1) - SB;
      mbar_wait(B_ZOK, 0);
      fence_async_global();
      mbar_wait(B_GO + 8, 0);
#pragma unroll 1
      for (int p = 0; p < 7; p++) {
        const uint32_t tile = g2_tile(p, w);
        const int col = g2_col(p, rank);
        mbar_wait(B_OUT + 16 * p + 8 * w, 0);
        fence_async_smem();
        if ((p & 1) || p == 6) {
          asm volatile("cp.reduce.async.bulk.tensor.2d.global.shared::cta.add.tile.bulk_group [%0, {%2, %3}], [%1];"
                       ::"l"(&maps.out), "r"(self(tile)), "r"(col), "r"(m * 128 + w * 64) : "memory");
        } else {
          asm volatile("cp.async.bulk.shared::cluster.shared::cta.mbarrier::complete_tx::bytes [%0], [%1], 8192, [%2];"
                       ::"r"(peer + out_tile(p + w)), "r"(self(tile)), "r"(peer + B_LFULL + 8 * (p + w)) : "memory");
        }
      }
      asm volatile("cp.async.bulk.commit_group;" ::: "memory");
      asm volatile("cp.async.bulk.wait_group.read 0;" ::: "memory");
      mbar_wait(B_RCVD, 0);
    };
    if (warp == 12) {
      if (!elect_one()) return;
      const int f0 = 224 * j;
      const int fh = (j & 1) ? f0 : f0 + 192;
      const int ff = (j & 1) ? f0 + 32 : f0;
      Ring r{0, 0};
#pragma unroll 1
      for (int s = 8; s < 14; s++) {
        if (s & 4) {
          mbar_wait(B_EMPTY + 8 * r.slot, r.phase);
          mbar_expect_tx(B_FULL + 8 * r.slot, 12288);
          tma3d(OFF_RING + r.slot * 16384, &maps.qkv, wcol, 32 * s, 0, B_FULL + 8 * r.slot);
          r.next();
        } else {
          const int e = s & 3;
          mbar_wait(B_EEMPTY + 8 * e, 0);
          mbar_expect_tx(B_EFULL + 8 * e, 12288);
          tma3d(OFF_E + e * 12288, &maps.qkv, wcol, 32 * s, 0, B_EFULL + 8 * e);
        }
      }
#pragma unroll 1
      for (int ps = 0; ps < 3; ps++) {
        if (ps == 2) {
#pragma unroll 1
          for (int s = 0; s < 4; s++) {
            const uint32_t fb = B_FULL + 8 * r.slot, dst = OFF_RING + r.slot * 16384;
            mbar_wait(B_EMPTY + 8 * r.slot, r.phase);
            mbar_expect_tx(fb, s < 3 ? 16384 : 8192);
            tma2d(dst, &maps.g32, fh, 128 * s, fb);
            tma2d(dst + 4096, &maps.u32, fh, 128 * s, fb);
            if (s < 3) {
              tma2d(dst + 8192, &maps.g32, fh, 128 * s + 64, fb);
              tma2d(dst + 12288, &maps.u32, fh, 128 * s + 64, fb);
            }
            r.next();
          }
        }
#pragma unroll 1
        for (int s = 0; s < 7; s++) {
          const uint32_t fb = B_FULL + 8 * r.slot, dst = OFF_RING + r.slot * 16384;
          mbar_wait(B_EMPTY + 8 * r.slot, r.phase);
          mbar_expect_tx(fb, 16384);
          tma2d(dst, &maps.g64, ff + 64 * ps, 64 * s, fb);
          tma2d(dst + 8192, &maps.u64, ff + 64 * ps, 64 * s, fb);
          r.next();
        }
      }
      uint32_t gb = 0;
#pragma unroll 1
      for (int c = 0; c < 7; c++) {
        if (c >= 3) {
          mbar_wait(B_GEMPTY + 8 * gb, c >= 6);
        } else if (c > 0) {
#pragma unroll 1
          for (int i = 0; i < 2; i++) {
            mbar_wait(B_EMPTY + 8 * r.slot, r.phase);
            r.next();
          }
          if (c == 2) {
            mbar_arrive(B_GO);
            mbar_wait(B_ZOK, 0);
            asm volatile("mbarrier.arrive.shared::cluster.b64 _, [%0];" ::"r"(in_cta(B_GO + 8, rank ^ 1)) : "memory");
          }
        }
        const uint32_t fb = B_GFULL + 8 * gb, dst = g2_buf(gb);
        mbar_expect_tx(fb, G2_BYTES);
        const int col = g2_col(c, rank);
        tma2d(dst, &maps.down64, col, ff, fb);
        tma2d(dst + 8192, &maps.down64, col, ff + 64, fb);
        tma2d(dst + 16384, &maps.down, col, fh, fb);
        tma2d(dst + 20480, &maps.down64, col, ff + 128, fb);
        tma2d(dst + 28672, &maps.wo, col, 56 * j, fb);
        gb = gb == 2 ? 0 : gb + 1;
      }
    } else if (warp == 13) {
      const uint32_t b = cta;
      mbar_wait(B_EPOCH, 0);
      const unsigned epoch = __float_as_uint(lds_f32(OFF_EPOCH));
      const int back = lane < 2 ? lane + 1 : 0;
      const unsigned* flag = &g_ex[m >= back ? b - 8 * back : b].flag;
      const int nB = min(5, 2 * m + 2), nsteps = nB + min(5, 2 * m + 1);
      auto key_block = [&](int n) { return n < nB ? 2 * m + 1 - (nB == 5 && n >= 3 ? 7 - n : n) : 2 * m + nB - n; };
      mbar_wait(B_K1RDY, 0);
      const int settle = epoch == 1 ? 1 : nsteps;
      int seen = 0;
#pragma unroll 1
      for (int n = 1; n <= nsteps; n++) {
        if (n == settle) {
          if (lane < 3) flag_wait(flag, epoch * 8 + 5);
          __syncwarp();
          fence_async_global();
          mbar_arrive_if(lane == 0, B_SETTLED);
        }
        if (n == nsteps) break;
        const int kv = key_block(n), kk = key_block(n + 1);
        const uint32_t fb = B_KVFULL + 8 * (n & 1);
        if (n < settle) {
          const int need = lane == 0 ? (m >= 2 || n == 1 ? min(n, 4) : min(n + 1, 4)) : (m < 2 ? 0 : (n < 4 ? n - 1 : (n < 7 ? 2 : 4)));
#pragma unroll 1
          for (uint32_t it = 0; __any_sync(~0u, lane < 2 && need && seen < need); it++) {
            unsigned v;
            asm volatile("ld.relaxed.gpu.global.u32 %0, [%1];" : "=r"(v) : "l"(flag) : "memory");
            seen = v - epoch * 8;
            if (it > POLL_LIMIT) __trap();
          }
          if (n < 4) mbar_wait(B_PUB + 8 * (m > 0 ? n - 1 : 2), 0);
          __syncwarp();
        }
        mbar_wait(B_KVEMPTY + 8 * ((n - 1) & 1), ((n - 1) >> 1) & 1);
        if (elect_one()) {
          mbar_expect_tx(fb, (n == 1 || n + 1 == nsteps) ? 8192 : 16384);
          if (n + 1 < nsteps) bulk_load(OFF_KV + ((n + 1) & 1) * 16384, kv_block(kk, j), 8192, fb);
          if (n > 1) bulk_load(OFF_KV + (n & 1) * 16384 + 8192, kv_block(kv, j) + 8192, 8192, fb);
        }
      }
      if (!elect_one()) return;
      ship(0);
    } else {
      if (warp == 14) {
        patch_gate(2, 14);
        mbar_wait(B_PUB + 16, 0);
        uint4* z = reinterpret_cast<uint4*>(out + (size_t)(m * 128 + j * 16) * 448);
#pragma unroll 4
        for (int i = 0; i < 28; i++) z[lane + i * 32] = make_uint4(0, 0, 0, 0);
        __syncwarp();
        mbar_arrive_if(lane < 4, B_ZRDY);
        return;
      }
      if (!elect_one()) return;
      mbar_wait(B_XFULL + 8 * 2, 0);
      const unsigned epoch = *(volatile unsigned*)&g_ex[cta].epoch + 1;
      sts32(OFF_EPOCH, epoch);
      mbar_arrive(B_EPOCH);
      *(volatile unsigned*)&g_ex[cta].epoch = epoch;
#pragma unroll 1
      for (int i = 0; i < 4; i++) {
        mbar_wait(i == 0 ? B_K1RDY : B_VRDY, 0);
        fence_async_smem();
        uint8_t* dst = g_ex[cta].kv[1 - (i >> 1)] + (i & 1) * 8192;
        asm volatile("cp.async.bulk.global.shared::cta.bulk_group [%0], [%1], 8192;" ::"l"(dst), "r"(self(OFF_KV + i * 8192)) : "memory");
        asm volatile("cp.async.bulk.commit_group;" ::: "memory");
        for (const uint32_t t0 = clock(); clock() - t0 < 300;) {}
        asm volatile("st.relaxed.gpu.global.u32 [%0], %1;" ::"l"(&g_ex[cta].flag), "r"(epoch * 8 + 1 + i) : "memory");
        asm volatile("cp.async.bulk.wait_group 0;" ::: "memory");
        if (i != 1) mbar_arrive(B_PUB + 8 * (i == 0 ? 0 : i - 1));
      }
      asm volatile("st.release.gpu.global.u32 [%0], %1;" ::"l"(&g_ex[cta].flag), "r"(epoch * 8 + 5) : "memory");
      mbar_wait(B_ZRDY, 0);
      asm volatile("red.release.gpu.global.add.u32 [%0], 1;" ::"l"(&g_zflag[m * 8]) : "memory");
      flag_wait(&g_zflag[m * 8], epoch * 8);
      mbar_arrive(B_ZOK);
      ship(1);
    }
  } else if (wg == 2) {
    const int t = threadIdx.x & 127;
    const bool lane0 = lane == 0;
    {
      const uint32_t r0 = t >> 3, ch = t & 7;
      const uint8_t* src = x + (size_t)(m * 128 + r0) * 896 + ch * 16;
      const uint32_t dst = OFF_X + r0 * 128 + ((ch ^ (r0 & 7)) << 4);
#pragma unroll 1
      for (int c = 2; c < 7 + XAHEAD; c++) {
        if (c < 7) {
#pragma unroll
          for (int i = 0; i < 8; i++)
            asm volatile("cp.async.cg.shared.global [%0], [%1], 16;" ::"r"(self(dst + c * 16384 + i * 2048)), "l"(src + c * 128 + i * 16 * 896) : "memory");
        }
        asm volatile("cp.async.commit_group;" ::: "memory");
        if (c >= XAHEAD) {
          asm volatile("cp.async.wait_group %0;" ::"n"(XAHEAD) : "memory");
          fence_async_smem();
          __syncwarp();
          mbar_arrive_if(lane0, B_XFULL + 8 * (c - XAHEAD));
        }
      }
    }
    asm volatile("setmaxnreg.inc.sync.aligned.u32 152;");
    const int wi = warp & 3, q = lane & 3;
    const int row0 = wi * 8 + (lane >> 2), row1 = 56 - wi * 8 + (lane >> 2);
    constexpr uint32_t QLO = desc_lo(OFF_QO, 16), KVLO = desc_lo(OFF_KV, 16);
    float sa[32], sb[32], o0[16], o1[16];
    uint32_t p[16];
    bool odd = false;
    float g0 = 0.f, g1 = 0.f;
    auto load_gate = [&](int w) {
      mbar_wait(B_GRDY, 0);
      g0 = lds_f32(OFF_G + (w * 64 + row0) * 4);
      g1 = lds_f32(OFF_G + (w * 64 + row1) * 4);
    };
    auto finalize = [&](int w, bool check) -> bool {
      const float l00 = __shfl_sync(~0u, odd ? o0[5] : o0[4], lane | 3), l01 = __shfl_sync(~0u, odd ? o0[7] : o0[6], lane | 3);
      const float l10 = __shfl_sync(~0u, odd ? o1[13] : o1[12], lane & ~3), l11 = __shfl_sync(~0u, odd ? o1[15] : o1[14], lane & ~3);
      if (check) {
        uint32_t d[4];
#pragma unroll
        for (int i = 0; i < 4; i++) {
          const float* o = (i < 2 ? o0 : o1) + 4 + 8 * (i & 1);
          const uint32_t e = __float_as_uint(o[0]) | __float_as_uint(o[2]), f = __float_as_uint(o[1]) | __float_as_uint(o[3]);
          d[i] = odd ? e : f;
        }
        const uint32_t da = (q & 1) ? d[0] : d[1], db = (q & 1) ? d[2] : d[3];
        const uint32_t dd = (q & 2) ? da : db;
        const float lo = fminf(fminf(l00, l01), fminf(l10, l11)), hi = l00 + l01 + l10 + l11;
        if (!__all_sync(~0u, (dd << 1) == 0 && lo >= 0x1p-40f && hi <= 0x1p100f)) return false;
      }
      const float i00 = g0 * rcp_fast(l00), i01 = g1 * rcp_fast(l01);
      const float i10 = g0 * rcp_fast(l10), i11 = g1 * rcp_fast(l11);
      uint32_t v[16];
#pragma unroll
      for (int g = 0; g < 4; g++) {
        v[2 * g] = pack_bf16(o0[4 * g] * i00, o0[4 * g + 1] * i00);
        v[2 * g + 1] = pack_bf16(o0[4 * g + 2] * i01, o0[4 * g + 3] * i01);
        v[8 + 2 * g] = pack_bf16(o1[4 * g] * i10, o1[4 * g + 1] * i10);
        v[8 + 2 * g + 1] = pack_bf16(o1[4 * g + 2] * i11, o1[4 * g + 3] * i11);
      }
#pragma unroll
      for (int g = 0; g < 4; g++) {
        const uint32_t* u = v + (g >> 1) + 8 * (g & 1);
        sts128(OFF_QO + w * 8192 + wi * 2048 + g * 512 + lane * 16, u[0], u[2], u[4], u[6]);
      }
      __syncwarp();
      mbar_arrive_if(lane0, B_ORDY + 8 * w);
      return true;
    };
    const uint32_t tri = ((2 * q <= (lane >> 2)) ? 0xffffu : 0u) | ((2 * q + 1 <= (lane >> 2)) ? 0xffff0000u : 0u);
    PMask mk;
#pragma unroll
    for (int k = 0; k < 4; k++) {
      mk.d[k] = k == wi ? tri : (k < wi ? ~0u : 0u);
      asm volatile("" : "+r"(mk.d[k]));
      mk.flip[k] = k == wi ? 0u : ~0u;
      asm volatile("" : "+r"(mk.flip[k]));
    }
#pragma unroll
    for (int i = 0; i < 16; i++) p[i] = 0u;
    mbar_wait(B_QKRDY + 8, 0);
    fence_async_smem();
    odd = __float_as_uint(lds_f32(OFF_EPOCH)) & 1;
    issue_s(sa, QLO + 512, KVLO);
    wg_wait<0>();
    reg_fence(sa);
    uint32_t ctl = m >= 2 ? 012000142001u : (m == 1 ? 010014001u : 01141u);
    asm volatile("" : "+r"(ctl));
    uint32_t qd = QLO + 512;
    uint32_t kd = KVLO, kp = KVLO - 512;
    int acc_prev = 0;
    uint32_t redo = 0;
    uint32_t gbar = B_VRDY, gpar = 0, ebar = B_KVEMPTY;
    int n = 0;
    auto step = [&](auto type) {
      constexpr int TYPE = decltype(type)::value;
      constexpr int SPLIT = TYPE == 2 ? 13 : 12;
      issue_s_pv(sb, qd + 4, kd + 4, o1, p, kp + 512 + 4, acc_prev);
      ex2_pairs<TYPE, 0, SPLIT>(sa);
      reg_fence(sa);
      const uint32_t landed = mbar_try(gbar, gpar);
      uint32_t qn = (ctl & 4) ? QLO : qd;
      uint32_t kn = (ctl >> 3) != 1 ? kd ^ 1024 : kd + 512;
      asm volatile("" : "+r"(qn), "+r"(kn));
      sched_fence();
      wg_wait<0>();
      reg_fence(o1);
      reg_fence(p);
      reg_fence(sb);
      mbar_arrive_if(lane0, ebar);
      ex2_pairs<TYPE, SPLIT, 16>(sa);
      pack_masked<TYPE>(sa, p, mk);
      if (TYPE == 1) {
        if (qd != QLO) {
          mbar_wait(B_VRDY, 0);
          fence_async_smem();
        } else if (!finalize(1, true)) {
          redo = 2;
        }
      }
      if (!landed) mbar_wait(gbar, gpar);
      issue_s_pv(sa, qn, kn, o0, p, kd + 512, TYPE != 1);
      ex2_pairs<TYPE, 0, SPLIT>(sb);
      reg_fence(sb);
      gbar = B_KVFULL + 8 * ((n + 1) & 1);
      gpar = (n >> 1) & 1;
      ebar ^= 8;
      kp = kd;
      kd ^= 1024;
      ctl >>= 3;
      acc_prev = TYPE != 1;
      asm volatile("" : "+r"(gbar), "+r"(gpar), "+r"(ebar), "+r"(kp), "+r"(kd), "+r"(ctl), "+r"(acc_prev));
      sched_fence();
      wg_wait<0>();
      sched_fence();
      reg_fence(o0);
      reg_fence(p);
      reg_fence(sa);
      ex2_pairs<TYPE, SPLIT, 16>(sb);
      pack_masked<TYPE>(sb, p, mk);
      if (TYPE == 1) load_gate(qd != QLO);
      qd = qn;
      n++;
    };
#pragma unroll 1
    do {
      if (!(ctl & 3)) step(Int<0>{});
      else if (ctl & 1) step(Int<1>{});
      else step(Int<2>{});
    } while (ctl != 1);
    issue_pv(o1, p, kp + 512 + 4, acc_prev);
    wg_wait<0>();
    reg_fence(o1);
    reg_fence(p);
    if (!finalize(0, true)) redo |= 1;
    uint32_t any;
    asm volatile("{\n.reg .pred p, q;\nsetp.ne.u32 p, %1, 0;\nbar.red.or.pred q, 1, 128, p;\nselp.u32 %0, 1, 0, q;\n}"
                 : "=r"(any) : "r"(redo) : "memory");
    if (any) {
      uint32_t ph = 0;
      RowStat r0{}, r1{};
      mbar_wait(B_SETTLED, 0);
#pragma unroll 1
      for (int w = 0; w < 2; w++) {
        const int cnt = min(5, 2 * m + 1 + w);
#pragma unroll 1
        for (int t = 0; t < cnt; t++) {
          asm volatile("bar.sync 1, 128;" ::: "memory");
          if (wi == 0 && elect_one()) {
            fence_async_global();
            mbar_expect_tx(B_SLOW, 16384);
            bulk_load(OFF_KV, kv_block(2 * m + w - t, j), 16384, B_SLOW);
          }
          mbar_wait(B_SLOW, ph);
          ph ^= 1;
          auto head = [&](float (&o)[16], RowStat& r, uint32_t hoff) {
            issue_s(sa, QLO + w * 512 + hoff, KVLO + hoff);
            wg_wait<0>();
            reg_fence(sa);
            if ((t & 3) == 0) mask_block(sa, t == 0, row0, row1, q);
            update_max(sa, r, t == 0);
            exp_shifted(sa, r.m0, r.m1);
            pack_p(sa, p);
#pragma unroll
            for (int g = 0; g < 4; g++) {
              o[4 * g] *= r.al0; o[4 * g + 1] *= r.al0; o[4 * g + 2] *= r.al1; o[4 * g + 3] *= r.al1;
            }
            issue_pv(o, p, KVLO + 512 + hoff, t != 0);
            wg_wait<0>();
            reg_fence(o);
            reg_fence(p);
          };
          head(o0, r0, 0);
          head(o1, r1, 4);
        }
        if ((redo >> w) & 1) {
          load_gate(w);
          finalize(w, false);
        }
      }
    }
    mbar_arrive_if(lane0, B_ATTDONE);
  } else {
    const int w = wg, wi = warp & 3, q = lane & 3;
    const bool lane0 = lane == 0;
    const int row = wi * 16 + (lane >> 2);
    const uint32_t xlo = desc_lo(OFF_X, 16) + w * 512;
    float acc[92];
    uint32_t vp[14], sh;
    const uint32_t srow = (wi * 16 + (lane & 7) + ((lane >> 3) & 1) * 8) * 128;
    {
      uint32_t prev = 0;
#pragma unroll
      for (int s = 0; s < 14; s++) {
        if (!(s & 1)) mbar_wait(B_XFULL + 4 * s, 0);
        const bool ring = s & 4;
        const uint32_t sl = s & 3;
        const uint32_t a = xlo + (s >> 1) * 1024 + (s & 1) * 4;
        const uint32_t b = (ring ? desc_lo(OFF_RING, 4096) + sl * 1024 : desc_lo(OFF_E, 4096) + sl * 768) + (j & 1);
        mbar_wait(B_GW + 8 * s, 0);
        fence_async_smem();
        wg_fence();
        mma_qkv(acc, a, b, DESC_HI, s);
        mma_qkv(acc, a + 2, b + 128, DESC_HI, 1);
        wg_commit();
        wg_wait<1>();
        mbar_arrive_if(lane0 && s > 0, prev);
        if (s == 6) asm volatile("setmaxnreg.inc.sync.aligned.u32 168;");
        prev = (ring ? B_EMPTY : B_EEMPTY) + 8 * sl;
      }
      mbar_wait(B_EPOCH, 0);
      sh = (__float_as_uint(lds_f32(OFF_EPOCH)) & 1) * 16;
      mbar_wait(B_EEMPTY + 8 * 3, 1);
      mbar_wait(B_FULL + 8 * (IT_P1 % NSLOT), (IT_P1 / NSLOT) & 1);
      wg_wait<0>();
      mbar_arrive_if(lane0, prev);
      reg_fence(acc);
    }
    uint32_t h[72];
    float a0, a1;
    float accA[64], accB[64], accH[32], accC[64];
    {
      const uint32_t kvt = OFF_KV + (1 - w) * 16384 + srow;
      {
        uint32_t v[14];
#pragma unroll
        for (int i = 0; i < 14; i++) v[i] = pack_bf16(acc[32 + 2 * i], acc[32 + 2 * i + 1]);
        store_heads(kvt, lane, v, 0x3F80u << sh);
        if (w == 1) {
          __syncwarp();
          mbar_arrive_if(lane0, B_K1RDY);
        }
      }
      {
        uint32_t v[14];
#pragma unroll
        for (int i = 0; i < 14; i++) v[i] = pack_bf16(acc[2 * i] * SM_C, acc[2 * i + 1] * SM_C);
        const uint32_t rg = 2 * wi + ((lane >> 3) & 1);
        store_heads(OFF_QO + w * 8192 + ((rg < 4 ? 2 * rg : 15 - 2 * rg) * 8 + (lane & 7)) * 128, lane, v, 0x71800000u >> sh);
      }
      __syncwarp();
      mbar_arrive_if(lane0, B_QKRDY + 8 * w);
#pragma unroll
      for (int i = 0; i < 14; i++) vp[i] = pack_bf16(acc[64 + 2 * i], acc[64 + 2 * i + 1]);
      reg_fence(vp);
      sched_fence();
    }
    uint32_t vpad;
    pass64<IT_P1, 0>(accA, xlo, lane0, [&](int hs) {
      if (hs == 0) {
        uint32_t big = 0;
#pragma unroll
        for (int i = 0; i < 14; i += 2) big = __vimax3_u16x2(big, vp[i] & 0x7fff7fffu, vp[i + 1] & 0x7fff7fffu);
        vpad = __any_sync(~0u, max(big >> 16, big & 0xffffu) >= 0x4980u) ? 0x3F803F80u : 0x3F80u << sh;
        asm volatile("" : "+r"(vpad));
      }
      if (hs == 1) {
        store_heads(OFF_KV + (1 - w) * 16384 + 8192 + srow, lane, vp, vpad);
        __syncwarp();
        mbar_arrive_if(lane0, B_VRDY);
      }
      if (hs == 2) {
        a0 = __expf(-__shfl_sync(~0u, acc[28], lane & ~3));
        a1 = __expf(-__shfl_sync(~0u, acc[30], lane & ~3));
        asm volatile("" : "+f"(a0), "+f"(a1));
      }
      if (hs == 3) {
        const float g0 = __fdividef(1.f, 1.f + a0), g1 = __fdividef(1.f, 1.f + a1);
        sts32(OFF_G + (w * 64 + row + (q & 1) * 8) * 4, __float_as_uint((q & 1) ? g1 : g0));
        a0 = 0.5f - 0.5f * g0;
        a1 = 0.5f - 0.5f * g1;
        __syncwarp();
        mbar_arrive_if(lane0, B_GRDY);
      }
    });
    pass64<IT_P2, 0>(accB, xlo, lane0, [&](int hs) {
      if (!(hs & 1)) glu_group<8>(h, accA, hs >> 1, a0, a1);
      if (hs == 1) glu_group<8>(h, accA, 7, a0, a1);
    });
    pass32<IT_P3>(accH, xlo, lane0, [&](int hs) {
      glu_group<8>(h + 16, accB, hs, a0, a1);
      if (hs == 0) glu_group<8>(h + 16, accB, 7, a0, a1);
    });
    pass64<IT_P4, 0>(accC, xlo, lane0, [&](int hs) { if (hs < 8 && !(hs & 1)) glu_group<4>(h + 32, accH, hs >> 1, a0, a1); });
    {
      float acc0[32], acc1[32];
      const uint32_t slot0 = wi * 2048 + ((lane & 7) + ((lane >> 3) & 1) * 8) * 128;
      auto slot = [&](int g) { return slot0 + (((2 * g + (lane >> 4)) ^ (lane & 7)) << 4); };
      auto mma_k = [&](float (&acc)[32], uint32_t b, int k) {
        mma_rs64(acc, h[4 * k], h[4 * k + 1], h[4 * k + 2], h[4 * k + 3], b + k * 128, DESC_HI, k);
      };
      {
        constexpr uint32_t b = desc_lo(g2_buf(0), 4096);
        mbar_wait(B_GFULL, 0);
        wg_fence();
#pragma unroll
        for (int k = 0; k < 4; k++) mma_k(acc0, b, k);
        wg_commit();
        sched_fence();
#pragma unroll
        for (int g = 0; g < 3; g++) glu_group<8>(h + 40, accC, g, a0, a1);
        wg_fence();
#pragma unroll
        for (int k = 4; k < 8; k++) mma_k(acc0, b, k);
        wg_commit();
        sched_fence();
#pragma unroll
        for (int g = 3; g < 6; g++) glu_group<8>(h + 40, accC, g, a0, a1);
        wg_fence();
#pragma unroll
        for (int k = 8; k < 12; k++) mma_k(acc0, b, k);
        wg_commit();
        sched_fence();
#pragma unroll
        for (int g = 6; g < 8; g++) glu_group<8>(h + 40, accC, g, a0, a1);
        mbar_wait(B_ORDY + 8 * w, 0);
#pragma unroll
        for (int g = 0; g < 4; g++) {
          const uint32_t rg = 2 * wi + (g >> 1);
          const uint4 r = lds128(OFF_QO + w * 8192 + (rg < 4 ? 2 * rg : 15 - 2 * rg) * 1024 + (g & 1) * 512 + lane * 16);
          uint32_t* u = h + 56 + (g >> 1) + 8 * (g & 1);
          u[0] = r.x; u[2] = r.y; u[4] = r.z; u[6] = r.w;
        }
#pragma unroll
        for (int i = 2; i < 14; i++) h[56 + i] = q >= (8 - i / 2) / 2 ? h[58 + i] : h[56 + i];
        h[70] = h[71] = 0u;
        wg_fence();
#pragma unroll
        for (int k = 12; k < 18; k++) mma_k(acc0, b, k);
        wg_commit();
        mbar_wait(B_GO, 0);
      }
      uint32_t gb = 1;
      auto fetch_peer = [&](uint4 (&x)[4], int p) {
        mbar_wait(B_LFULL + 8 * (2 * ((p >> 1) - 1) + w), 0);
#pragma unroll
        for (int g = 0; g < 4; g++) x[g] = lds128(g2_tile(p, w) + slot(g));
      };
      auto stage_sum = [&](const uint32_t (&v)[16], const uint4 (&x)[4], int p) {
#pragma unroll
        for (int g = 0; g < 4; g++)
          stsm4(g2_tile(p, w) + slot(g), add_bf16x2(v[4 * g], x[g].x), add_bf16x2(v[4 * g + 1], x[g].y),
                add_bf16x2(v[4 * g + 2], x[g].z), add_bf16x2(v[4 * g + 3], x[g].w));
        __syncwarp();
        mbar_arrive_if(lane0, B_OUT + 16 * p + 8 * w);
      };
      auto chunk = [&](float (&acc)[32], float (&prv)[32], int c, bool send) {
        const uint32_t b = desc_lo(0, 4096) + (g2_buf(gb) >> 4);
        mbar_wait(B_GFULL + 8 * gb, c >= 3 && c < 6);
        wg_fence();
#pragma unroll
        for (int k = 0; k < G2A; k++) mma_k(acc, b, k);
        wg_commit();
        wg_wait<1>();
        reg_fence(prv);
        mbar_arrive_if(lane0, B_GEMPTY + 8 * (gb == 0 ? 2 : gb - 1));
        uint32_t v[16];
#pragma unroll
        for (int i = 0; i < 16; i++) v[i] = pack_bf16(prv[2 * i], prv[2 * i + 1]);
        if (send) {
          if (c == 3) mbar_wait(B_ATTDONE, 0);
#pragma unroll
          for (int g = 0; g < 4; g++) sts128(g2_tile(c - 1, w) + slot(g), v[4 * g], v[4 * g + 1], v[4 * g + 2], v[4 * g + 3]);
          __syncwarp();
          mbar_arrive_if(lane0, B_OUT + 16 * (c - 1) + 8 * w);
          wg_fence();
#pragma unroll
          for (int k = G2A; k < 18; k++) mma_k(acc, b, k);
          wg_commit();
        } else {
          uint4 x[4] = {};
          reg_fence(v);
          if (c > 2) fetch_peer(x, c - 1);
          else mbar_wait(B_OUT + 8 * w, 0);
          wg_fence();
#pragma unroll
          for (int k = G2A; k < G2B; k++) mma_k(acc, b, k);
          wg_commit();
          sched_fence();
          stage_sum(v, x, c - 1);
          wg_fence();
#pragma unroll
          for (int k = G2B; k < 18; k++) mma_k(acc, b, k);
          wg_commit();
        }
        gb = gb == 2 ? 0 : gb + 1;
      };
#pragma unroll 1
      for (int c = 1; c < 7; c += 2) {
        chunk(acc1, acc0, c, true);
        chunk(acc0, acc1, c + 1, false);
      }
      {
        uint32_t v[16];
        uint4 x[4];
        fetch_peer(x, 6);
        if (lane0) asm volatile("mbarrier.arrive.shared::cluster.b64 _, [%0];" ::"r"(in_cta(B_RCVD, rank ^ 1)) : "memory");
        sched_fence();
        wg_wait<0>();
        reg_fence(acc0);
#pragma unroll
        for (int i = 0; i < 16; i++) v[i] = pack_bf16(acc0[2 * i], acc0[2 * i + 1]);
        stage_sum(v, x, 6);
      }
    }
  }
}

typedef CUresult (*EncodeFn)(CUtensorMap*, CUtensorMapDataType, cuuint32_t, void*, const cuuint64_t*, const cuuint64_t*,
                             const cuuint32_t*, const cuuint32_t*, CUtensorMapInterleave, CUtensorMapSwizzle,
                             CUtensorMapL2promotion, CUtensorMapFloatOOBfill);

void encode(EncodeFn fn, CUtensorMap* m, const void* p, int rank, const cuuint64_t* dims, const cuuint64_t* strides,
            const cuuint32_t* box, CUtensorMapSwizzle sw = CU_TENSOR_MAP_SWIZZLE_128B) {
  const cuuint32_t es[3] = {1, 1, 1};
  fn(m, CU_TENSOR_MAP_DATA_TYPE_BFLOAT16, rank, const_cast<void*>(p), dims, strides, box, es, CU_TENSOR_MAP_INTERLEAVE_NONE,
     sw, CU_TENSOR_MAP_L2_PROMOTION_L2_128B, CU_TENSOR_MAP_FLOAT_OOB_FILL_NONE);
}
void encode2d(EncodeFn fn, CUtensorMap* m, const void* p, uint64_t cols, uint64_t rows, uint32_t bc, uint32_t br,
              CUtensorMapSwizzle sw = CU_TENSOR_MAP_SWIZZLE_128B) {
  const cuuint64_t dims[2] = {cols, rows}, strides[1] = {cols * 2};
  const cuuint32_t box[2] = {bc, br};
  encode(fn, m, p, 2, dims, strides, box, sw);
}

}

extern "C" void kernel_launch(void* const* d_in, const int* in_sizes, int n_in, void* d_out, int out_size) {
  (void)in_sizes; (void)n_in; (void)out_size;
  void* fp = nullptr;
  cudaDriverEntryPointQueryResult qr;
  cudaGetDriverEntryPoint("cuTensorMapEncodeTiled", &fp, cudaEnableDefault, &qr);
  EncodeFn fn = (EncodeFn)fp;
  Maps maps;
  {
    const cuuint64_t dims[3] = {448, 448, 3}, strides[2] = {1344 * 2, 448 * 2};
    const cuuint32_t box[3] = {64, 32, 3};
    encode(fn, &maps.qkv, d_in[1], 3, dims, strides, box);
  }
  encode2d(fn, &maps.g64, d_in[4], 1792, 448, 64, 64);
  encode2d(fn, &maps.g32, d_in[4], 1792, 448, 32, 64, CU_TENSOR_MAP_SWIZZLE_64B);
  encode2d(fn, &maps.u64, d_in[5], 1792, 448, 64, 64);
  encode2d(fn, &maps.u32, d_in[5], 1792, 448, 32, 64, CU_TENSOR_MAP_SWIZZLE_64B);
  encode2d(fn, &maps.down, d_in[6], 448, 1792, 64, 32);
  encode2d(fn, &maps.down64, d_in[6], 448, 1792, 64, 64);
  encode2d(fn, &maps.wo, d_in[2], 448, 448, 64, 64);
  encode2d(fn, &maps.out, d_out, 448, 2048, 64, 64);
  cudaFuncSetAttribute(fused_kernel, cudaFuncAttributeMaxDynamicSharedMemorySize, SMEM_BYTES);
  fused_kernel<<<128, 512, SMEM_BYTES>>>((const uint8_t*)d_in[0], (const uint8_t*)d_in[1], (const __nv_bfloat16*)d_in[7],
                                         (__nv_bfloat16*)d_out, maps);
}
```
